```python
import torch

def _softmax(x, axis=-1):
    return torch.softmax(x, dim=axis)
def _gelu(x):
    return torch.nn.functional.gelu(x, approximate="tanh")
def _silu(x):
    return torch.nn.functional.silu(x)
def _sigmoid(x):
    return torch.sigmoid(x)
def _layernorm(x, axis=-1, eps=1e-5):
    m = x.mean(dim=axis, keepdim=True)
    v = x.var(dim=axis, keepdim=True, unbiased=False)
    return (x - m) / torch.sqrt(v + eps)
def _scatter_add(tgt, idx, src, axis=0):
    return tgt.clone().index_add_(axis, idx, src)
def _segment_sum(src, seg, n):
    out = torch.zeros((n,) + src.shape[1:], dtype=src.dtype)
    return out.index_add_(0, seg, src)
def _pad(x, pw):
    flat = tuple(v for pair in reversed(pw) for v in pair)
    return torch.nn.functional.pad(x, flat)

kernel_name = 'recurrent_scan__mha_block_cached__mixer_channel_mlp__prompt'

def setup_inputs():

    _w = (lambda a: (lambda t: t.to(torch.bfloat16) if t.is_floating_point() else t)(torch.as_tensor(a)))
    def _A_setup():
        B, Sq, D = 1, 2048, 512
        H, Sk, Dh = 32, 2048, 128
        return {
            "x": _w((lambda *s: torch.randn(*s, dtype=torch.bfloat16) * 0.05)(B, Sq, D)),
            "k_cache": _w((lambda *s: torch.randn(*s, dtype=torch.bfloat16) * 1.6)(B, H, Sk, Dh)),
            "v_cache": _w((lambda *s: torch.randn(*s, dtype=torch.bfloat16) * 0.8)(B, H, Sk, Dh)),
            "wq": _w((lambda *s: torch.randn(*s, dtype=torch.bfloat16) * 1.6)(D, H * Dh) * (D ** -0.5)),
            "wo": _w((lambda *s: torch.randn(*s, dtype=torch.bfloat16) * 0.8)(H * Dh, D) * ((H * Dh) ** -0.5)),
        }
    _A_in = _A_setup()

    def _B_setup():
        B, S, D, F = 1, 2048, 512, 1376
        return {
            "x": _w((lambda *s: torch.randn(*s, dtype=torch.bfloat16) * 0.05)(B, S, D)),
            "w1": _w((lambda *s: torch.randn(*s, dtype=torch.bfloat16) * 1.6)(D, F) * (D ** -0.5)),
            "b1": _w((lambda *s: torch.randn(*s, dtype=torch.bfloat16) * 0.8)(F)),
            "w2": _w((lambda *s: torch.randn(*s, dtype=torch.bfloat16) * 0.2)(F, D) * (F ** -0.5)),
            "b2": _w((lambda *s: torch.randn(*s, dtype=torch.bfloat16) * 0.2)(D)),
        }
    _B_in = _B_setup()

    return {
        "A_x": _A_in["x"],
        "A_k_cache": _A_in["k_cache"],
        "A_v_cache": _A_in["v_cache"],
        "A_wq": _A_in["wq"],
        "A_wo": _A_in["wo"],
        "B_x": _B_in["x"],
        "B_w1": _B_in["w1"],
        "B_b1": _B_in["b1"],
        "B_w2": _B_in["w2"],
        "B_b2": _B_in["b2"],
    }

def reference(A_x, A_k_cache, A_v_cache, A_wq, A_wo, B_x, B_w1, B_b1, B_w2, B_b2):
    def _A_ref(x, k_cache, v_cache, wq, wo):
        B, Sq, D = x.shape
        H, Dh = 32, 128
        q = (lambda x, *d: x.permute(*d))((x @ wq).reshape(B, Sq, H, Dh), 0, 2, 1, 3)
        scores = torch.einsum("bhqd,bhkd->bhqk", q, k_cache) * (Dh ** -0.5)
        p = _softmax(scores, axis=-1)
        o = torch.einsum("bhqk,bhkd->bhqd", p, v_cache)
        return (lambda x, *d: x.permute(*d))(o, 0, 2, 1, 3).reshape(B, Sq, H * Dh) @ wo

    def _B_ref(x, w1, b1, w2, b2):
        y = _layernorm(x, axis=-1)
        h = _gelu(torch.einsum("bsd,df->bsf", y, w1) + b1)
        return torch.einsum("bsf,fd->bsd", h, w2) + b2

    x = A_x
    xn = _layernorm(x, axis=-1)
    s = _A_ref(xn, A_k_cache, A_v_cache, A_wq, A_wo)
    g = _silu(_B_ref(xn, B_w1, B_b1, B_w2, B_b2))
    return x + s * g
```

```cpp
#include <cuda_runtime.h>
#include <cuda_bf16.h>
#include <cuda.h>
#include <stdint.h>

typedef __nv_bfloat16 bf16;

constexpr int SEQ = 2048;
constexpr int DM  = 512;
constexpr int NH  = 32;
constexpr int DH  = 128;
constexpr int HD  = NH * DH;
constexpr int FF  = 1376;

__device__ bf16 g_xn[SEQ * DM];
__device__ bf16 g_y [SEQ * DM];
__device__ bf16 g_q [SEQ * HD];
__device__ bf16 g_h [SEQ * FF];
__device__ bf16 g_o [SEQ * HD];

__device__ __forceinline__ uint32_t smem_u32(const void* p) {
    return (uint32_t)__cvta_generic_to_shared(p);
}
__device__ __forceinline__ void mbar_init(uint32_t bar, uint32_t count) {
    asm volatile("mbarrier.init.shared::cta.b64 [%0], %1;" :: "r"(bar), "r"(count) : "memory");
}
__device__ __forceinline__ void mbar_arrive(uint32_t bar) {
    asm volatile("mbarrier.arrive.shared::cta.b64 _, [%0];" :: "r"(bar) : "memory");
}
__device__ __forceinline__ void mbar_expect_tx(uint32_t bar, uint32_t bytes) {
    asm volatile("mbarrier.arrive.expect_tx.shared::cta.b64 _, [%0], %1;" :: "r"(bar), "r"(bytes) : "memory");
}
__device__ __forceinline__ void mbar_wait(uint32_t bar, uint32_t parity) {
    asm volatile(
        "{\n"
        ".reg .pred p;\n"
        "LAB_WAIT:\n"
        "mbarrier.try_wait.parity.shared::cta.b64 p, [%0], %1;\n"
        "@p bra DONE;\n"
        "bra LAB_WAIT;\n"
        "DONE:\n"
        "}\n" :: "r"(bar), "r"(parity) : "memory");
}
__device__ __forceinline__ void tma_load_2d(uint32_t dst, const CUtensorMap* map, uint32_t bar, int c0, int c1) {
    asm volatile(
        "cp.async.bulk.tensor.2d.shared::cluster.global.mbarrier::complete_tx::bytes [%0], [%1, {%3, %4}], [%2];"
        :: "r"(dst), "l"((uint64_t)map), "r"(bar), "r"(c0), "r"(c1) : "memory");
}
__device__ __forceinline__ void wgmma_fence() { asm volatile("wgmma.fence.sync.aligned;" ::: "memory"); }
__device__ __forceinline__ void wgmma_commit() { asm volatile("wgmma.commit_group.sync.aligned;" ::: "memory"); }
template <int N> __device__ __forceinline__ void wgmma_wait() {
    asm volatile("wgmma.wait_group.sync.aligned %0;" :: "n"(N) : "memory");
}
template <int R> __device__ __forceinline__ void reg_alloc() {
    asm volatile("setmaxnreg.inc.sync.aligned.u32 %0;" :: "n"(R));
}
template <int R> __device__ __forceinline__ void reg_dealloc() {
    asm volatile("setmaxnreg.dec.sync.aligned.u32 %0;" :: "n"(R));
}
__device__ __forceinline__ void fence_barrier_init() {
    asm volatile("fence.mbarrier_init.release.cluster;" ::: "memory");
}
__device__ __forceinline__ void fence_proxy_async() {
    asm volatile("fence.proxy.async.shared::cta;" ::: "memory");
}

__device__ __forceinline__ uint64_t make_desc(uint32_t addr, uint32_t lbo_bytes, uint32_t sbo_bytes) {
    uint64_t d = 0;
    d |= (uint64_t)((addr & 0x3FFFF) >> 4);
    d |= (uint64_t)((lbo_bytes & 0x3FFFF) >> 4) << 16;
    d |= (uint64_t)((sbo_bytes & 0x3FFFF) >> 4) << 32;
    d |= (uint64_t)1 << 62;
    return d;
}

template <int TA, int TB>
__device__ __forceinline__ void wgmma_m64n128k16_ss(float (&d)[64], uint64_t da, uint64_t db, int scale_d) {
    asm volatile(
        "{\n.reg .pred p;\nsetp.ne.b32 p, %66, 0;\n"
        "wgmma.mma_async.sync.aligned.m64n128k16.f32.bf16.bf16 "
        "{%0,%1,%2,%3,%4,%5,%6,%7,%8,%9,%10,%11,%12,%13,%14,%15,"
        "%16,%17,%18,%19,%20,%21,%22,%23,%24,%25,%26,%27,%28,%29,%30,%31,"
        "%32,%33,%34,%35,%36,%37,%38,%39,%40,%41,%42,%43,%44,%45,%46,%47,"
        "%48,%49,%50,%51,%52,%53,%54,%55,%56,%57,%58,%59,%60,%61,%62,%63},"
        " %64, %65, p, 1, 1, %67, %68;\n}\n"
        : "+f"(d[0]), "+f"(d[1]), "+f"(d[2]), "+f"(d[3]), "+f"(d[4]), "+f"(d[5]), "+f"(d[6]), "+f"(d[7]),
          "+f"(d[8]), "+f"(d[9]), "+f"(d[10]), "+f"(d[11]), "+f"(d[12]), "+f"(d[13]), "+f"(d[14]), "+f"(d[15]),
          "+f"(d[16]), "+f"(d[17]), "+f"(d[18]), "+f"(d[19]), "+f"(d[20]), "+f"(d[21]), "+f"(d[22]), "+f"(d[23]),
          "+f"(d[24]), "+f"(d[25]), "+f"(d[26]), "+f"(d[27]), "+f"(d[28]), "+f"(d[29]), "+f"(d[30]), "+f"(d[31]),
          "+f"(d[32]), "+f"(d[33]), "+f"(d[34]), "+f"(d[35]), "+f"(d[36]), "+f"(d[37]), "+f"(d[38]), "+f"(d[39]),
          "+f"(d[40]), "+f"(d[41]), "+f"(d[42]), "+f"(d[43]), "+f"(d[44]), "+f"(d[45]), "+f"(d[46]), "+f"(d[47]),
          "+f"(d[48]), "+f"(d[49]), "+f"(d[50]), "+f"(d[51]), "+f"(d[52]), "+f"(d[53]), "+f"(d[54]), "+f"(d[55]),
          "+f"(d[56]), "+f"(d[57]), "+f"(d[58]), "+f"(d[59]), "+f"(d[60]), "+f"(d[61]), "+f"(d[62]), "+f"(d[63])
        : "l"(da), "l"(db), "r"(scale_d), "n"(TA), "n"(TB));
}

template <int TB>
__device__ __forceinline__ void wgmma_m64n128k16_rs(float (&d)[64], uint32_t a0, uint32_t a1, uint32_t a2, uint32_t a3,
                                                    uint64_t db, int scale_d) {
    asm volatile(
        "{\n.reg .pred p;\nsetp.ne.b32 p, %69, 0;\n"
        "wgmma.mma_async.sync.aligned.m64n128k16.f32.bf16.bf16 "
        "{%0,%1,%2,%3,%4,%5,%6,%7,%8,%9,%10,%11,%12,%13,%14,%15,"
        "%16,%17,%18,%19,%20,%21,%22,%23,%24,%25,%26,%27,%28,%29,%30,%31,"
        "%32,%33,%34,%35,%36,%37,%38,%39,%40,%41,%42,%43,%44,%45,%46,%47,"
        "%48,%49,%50,%51,%52,%53,%54,%55,%56,%57,%58,%59,%60,%61,%62,%63},"
        " {%64,%65,%66,%67}, %68, p, 1, 1, %70;\n}\n"
        : "+f"(d[0]), "+f"(d[1]), "+f"(d[2]), "+f"(d[3]), "+f"(d[4]), "+f"(d[5]), "+f"(d[6]), "+f"(d[7]),
          "+f"(d[8]), "+f"(d[9]), "+f"(d[10]), "+f"(d[11]), "+f"(d[12]), "+f"(d[13]), "+f"(d[14]), "+f"(d[15]),
          "+f"(d[16]), "+f"(d[17]), "+f"(d[18]), "+f"(d[19]), "+f"(d[20]), "+f"(d[21]), "+f"(d[22]), "+f"(d[23]),
          "+f"(d[24]), "+f"(d[25]), "+f"(d[26]), "+f"(d[27]), "+f"(d[28]), "+f"(d[29]), "+f"(d[30]), "+f"(d[31]),
          "+f"(d[32]), "+f"(d[33]), "+f"(d[34]), "+f"(d[35]), "+f"(d[36]), "+f"(d[37]), "+f"(d[38]), "+f"(d[39]),
          "+f"(d[40]), "+f"(d[41]), "+f"(d[42]), "+f"(d[43]), "+f"(d[44]), "+f"(d[45]), "+f"(d[46]), "+f"(d[47]),
          "+f"(d[48]), "+f"(d[49]), "+f"(d[50]), "+f"(d[51]), "+f"(d[52]), "+f"(d[53]), "+f"(d[54]), "+f"(d[55]),
          "+f"(d[56]), "+f"(d[57]), "+f"(d[58]), "+f"(d[59]), "+f"(d[60]), "+f"(d[61]), "+f"(d[62]), "+f"(d[63])
        : "r"(a0), "r"(a1), "r"(a2), "r"(a3), "l"(db), "r"(scale_d), "n"(TB));
}

__device__ __forceinline__ uint32_t pack_bf16(float lo, float hi) {
    __nv_bfloat162 v = __floats2bfloat162_rn(lo, hi);
    return *reinterpret_cast<uint32_t*>(&v);
}

__global__ void __launch_bounds__(256) ln_kernel(const bf16* __restrict__ x) {
    int warp = threadIdx.x >> 5, lane = threadIdx.x & 31;
    int row = blockIdx.x * 8 + warp;
    const uint4* src = reinterpret_cast<const uint4*>(x + (size_t)row * DM);
    float v[16];
#pragma unroll
    for (int i = 0; i < 2; i++) {
        uint4 u = src[lane + i * 32];
        const __nv_bfloat162* h = reinterpret_cast<const __nv_bfloat162*>(&u);
#pragma unroll
        for (int j = 0; j < 4; j++) {
            float2 f = __bfloat1622float2(h[j]);
            v[i * 8 + j * 2] = f.x; v[i * 8 + j * 2 + 1] = f.y;
        }
    }
#pragma unroll
    for (int pass = 0; pass < 2; pass++) {
        float s = 0.f;
#pragma unroll
        for (int i = 0; i < 16; i++) s += v[i];
#pragma unroll
        for (int o = 16; o > 0; o >>= 1) s += __shfl_xor_sync(0xffffffffu, s, o);
        float mean = s * (1.f / DM);
        float q = 0.f;
#pragma unroll
        for (int i = 0; i < 16; i++) { float d = v[i] - mean; q += d * d; }
#pragma unroll
        for (int o = 16; o > 0; o >>= 1) q += __shfl_xor_sync(0xffffffffu, q, o);
        float rstd = 1.0f / sqrtf(q * (1.f / DM) + 1e-5f);
        bf16* dst = (pass == 0 ? g_xn : g_y) + (size_t)row * DM;
#pragma unroll
        for (int i = 0; i < 2; i++) {
            uint4 u;
            uint32_t* w = reinterpret_cast<uint32_t*>(&u);
#pragma unroll
            for (int j = 0; j < 4; j++) {
                __nv_bfloat162 h = __floats2bfloat162_rn((v[i * 8 + j * 2] - mean) * rstd, (v[i * 8 + j * 2 + 1] - mean) * rstd);
                w[j] = *reinterpret_cast<uint32_t*>(&h);
                float2 f = __bfloat1622float2(h);
                v[i * 8 + j * 2] = f.x; v[i * 8 + j * 2 + 1] = f.y;
            }
            reinterpret_cast<uint4*>(dst)[lane + i * 32] = u;
        }
    }
}

constexpr int G_STAGES = 4;
constexpr int G_STAGE_BYTES = 32768;
constexpr int G_SMEM = G_STAGES * G_STAGE_BYTES + 1024 + 256;

__device__ __forceinline__ float gelu_tanh(float x) {
    float u = 0.7978845608028654f * (x + 0.044715f * x * x * x);
    float t = 1.f - 2.f / (1.f + __expf(2.f * u));
    return 0.5f * x * (1.f + t);
}

template <int MODE>
__global__ void __launch_bounds__(384, 1)
gemm_kernel(const __grid_constant__ CUtensorMap mapA, const __grid_constant__ CUtensorMap mapB,
            bf16* __restrict__ C, int ldc, int N, int K, const bf16* __restrict__ bias) {
    extern __shared__ uint8_t smem_raw[];
    uint32_t sbase = (smem_u32(smem_raw) + 1023) & ~1023u;
    uint32_t bar_full = sbase + G_STAGES * G_STAGE_BYTES;
    uint32_t bar_empty = bar_full + 8 * G_STAGES;
    int wg = threadIdx.x >> 7;
    int tid = threadIdx.x & 127;
    int m0 = blockIdx.y * 128, n0 = blockIdx.x * 128;
    int nk = K / 64;

    if (threadIdx.x == 0) {
        for (int i = 0; i < G_STAGES; i++) { mbar_init(bar_full + 8 * i, 1); mbar_init(bar_empty + 8 * i, 8); }
        fence_barrier_init();
    }
    __syncthreads();

    if (wg == 0) {
        reg_dealloc<40>();
        if (tid == 0) {
            for (int it = 0; it < nk; it++) {
                int s = it % G_STAGES;
                uint32_t ph = (it / G_STAGES) & 1;
                mbar_wait(bar_empty + 8 * s, ph ^ 1);
                mbar_expect_tx(bar_full + 8 * s, G_STAGE_BYTES);
                uint32_t a = sbase + s * G_STAGE_BYTES;
                tma_load_2d(a, &mapA, bar_full + 8 * s, it * 64, m0);
                tma_load_2d(a + 16384, &mapB, bar_full + 8 * s, n0, it * 64);
                tma_load_2d(a + 16384 + 8192, &mapB, bar_full + 8 * s, n0 + 64, it * 64);
            }
        }
    } else {
        reg_alloc<232>();
        float acc[64];
#pragma unroll
        for (int i = 0; i < 64; i++) acc[i] = 0.f;
        int cw = wg - 1;
        for (int it = 0; it < nk; it++) {
            int s = it % G_STAGES;
            uint32_t ph = (it / G_STAGES) & 1;
            mbar_wait(bar_full + 8 * s, ph);
            uint32_t a = sbase + s * G_STAGE_BYTES + cw * 8192;
            uint32_t b = sbase + s * G_STAGE_BYTES + 16384;
            wgmma_fence();
#pragma unroll
            for (int kk = 0; kk < 4; kk++) {
                wgmma_m64n128k16_ss<0, 1>(acc, make_desc(a + kk * 32, 16, 1024), make_desc(b + kk * 2048, 8192, 1024), 1);
            }
            wgmma_commit();
            wgmma_wait<0>();
            if ((tid & 31) == 0) mbar_arrive(bar_empty + 8 * s);
        }
        int warp = tid >> 5, lane = tid & 31;
        int r0 = m0 + cw * 64 + warp * 16 + (lane >> 2);
#pragma unroll
        for (int j = 0; j < 16; j++) {
            int c = n0 + j * 8 + (lane & 3) * 2;
            if (c < N) {
                float v0 = acc[j * 4 + 0], v1 = acc[j * 4 + 1], v2 = acc[j * 4 + 2], v3 = acc[j * 4 + 3];
                if (MODE == 1) {
                    float b0 = __bfloat162float(bias[c]), b1 = __bfloat162float(bias[c + 1]);
                    v0 = gelu_tanh(v0 + b0); v1 = gelu_tanh(v1 + b1);
                    v2 = gelu_tanh(v2 + b0); v3 = gelu_tanh(v3 + b1);
                }
                *reinterpret_cast<uint32_t*>(C + (size_t)r0 * ldc + c) = pack_bf16(v0, v1);
                *reinterpret_cast<uint32_t*>(C + (size_t)(r0 + 8) * ldc + c) = pack_bf16(v2, v3);
            }
        }
    }
}

constexpr int A_KV_STAGES = 2;
constexpr int A_TILE_BYTES = 128 * 128 * 2;
constexpr int A_SMEM = A_TILE_BYTES * (1 + 2 * A_KV_STAGES) + 1024 + 256;

__global__ void __launch_bounds__(384, 1)
attn_kernel(const __grid_constant__ CUtensorMap mapQ, const __grid_constant__ CUtensorMap mapK,
            const __grid_constant__ CUtensorMap mapV) {
    extern __shared__ uint8_t smem_raw[];
    uint32_t sbase = (smem_u32(smem_raw) + 1023) & ~1023u;
    uint32_t sQ = sbase;
    uint32_t sK = sQ + A_TILE_BYTES;
    uint32_t sV = sK + A_KV_STAGES * A_TILE_BYTES;
    uint32_t bars = sV + A_KV_STAGES * A_TILE_BYTES;
    uint32_t bar_q = bars;
    uint32_t bar_kf = bars + 8, bar_ke = bar_kf + 8 * A_KV_STAGES;
    uint32_t bar_vf = bar_ke + 8 * A_KV_STAGES, bar_ve = bar_vf + 8 * A_KV_STAGES;
    int wg = threadIdx.x >> 7;
    int tid = threadIdx.x & 127;
    int qt = blockIdx.x, head = blockIdx.y;
    constexpr int NT = SEQ / 128;

    if (threadIdx.x == 0) {
        mbar_init(bar_q, 1);
        for (int i = 0; i < A_KV_STAGES; i++) {
            mbar_init(bar_kf + 8 * i, 1); mbar_init(bar_ke + 8 * i, 8);
            mbar_init(bar_vf + 8 * i, 1); mbar_init(bar_ve + 8 * i, 8);
        }
        fence_barrier_init();
    }
    __syncthreads();

    if (wg == 0) {
        reg_dealloc<40>();
        if (tid == 0) {
            mbar_expect_tx(bar_q, A_TILE_BYTES);
            tma_load_2d(sQ, &mapQ, bar_q, head * DH, qt * 128);
            tma_load_2d(sQ + 16384, &mapQ, bar_q, head * DH + 64, qt * 128);
            for (int it = 0; it < NT; it++) {
                int s = it % A_KV_STAGES;
                uint32_t ph = (it / A_KV_STAGES) & 1;
                int row = head * SEQ + it * 128;
                mbar_wait(bar_ke + 8 * s, ph ^ 1);
                mbar_expect_tx(bar_kf + 8 * s, A_TILE_BYTES);
                tma_load_2d(sK + s * A_TILE_BYTES, &mapK, bar_kf + 8 * s, 0, row);
                tma_load_2d(sK + s * A_TILE_BYTES + 16384, &mapK, bar_kf + 8 * s, 64, row);
                mbar_wait(bar_ve + 8 * s, ph ^ 1);
                mbar_expect_tx(bar_vf + 8 * s, A_TILE_BYTES);
                tma_load_2d(sV + s * A_TILE_BYTES, &mapV, bar_vf + 8 * s, 0, row);
                tma_load_2d(sV + s * A_TILE_BYTES + 16384, &mapV, bar_vf + 8 * s, 64, row);
            }
        }
    } else {
        reg_alloc<232>();
        int cw = wg - 1;
        int warp = tid >> 5, lane = tid & 31;
        float o[64];
#pragma unroll
        for (int i = 0; i < 64; i++) o[i] = 0.f;
        float m0 = -INFINITY, m1 = -INFINITY, l0 = 0.f, l1 = 0.f;
        const float sc = 0.08838834764831845f * 1.4426950408889634f;
        mbar_wait(bar_q, 0);
        uint32_t qa = sQ + cw * 8192;
        for (int it = 0; it < NT; it++) {
            int s = it % A_KV_STAGES;
            uint32_t ph = (it / A_KV_STAGES) & 1;
            float sacc[64];
            mbar_wait(bar_kf + 8 * s, ph);
            uint32_t kb = sK + s * A_TILE_BYTES;
            wgmma_fence();
#pragma unroll
            for (int kk = 0; kk < 8; kk++) {
                uint32_t off = (kk >> 2) * 16384 + (kk & 3) * 32;
                wgmma_m64n128k16_ss<0, 0>(sacc, make_desc(qa + off, 16, 1024), make_desc(kb + off, 16, 1024), kk != 0);
            }
            wgmma_commit();
            wgmma_wait<0>();
            if (lane == 0) mbar_arrive(bar_ke + 8 * s);
            float mx0 = m0, mx1 = m1;
#pragma unroll
            for (int j = 0; j < 16; j++) {
                mx0 = fmaxf(mx0, fmaxf(sacc[j * 4 + 0], sacc[j * 4 + 1]));
                mx1 = fmaxf(mx1, fmaxf(sacc[j * 4 + 2], sacc[j * 4 + 3]));
            }
            mx0 = fmaxf(mx0, __shfl_xor_sync(0xffffffffu, mx0, 1));
            mx0 = fmaxf(mx0, __shfl_xor_sync(0xffffffffu, mx0, 2));
            mx1 = fmaxf(mx1, __shfl_xor_sync(0xffffffffu, mx1, 1));
            mx1 = fmaxf(mx1, __shfl_xor_sync(0xffffffffu, mx1, 2));
            float c0 = exp2f((m0 - mx0) * sc), c1 = exp2f((m1 - mx1) * sc);
            m0 = mx0; m1 = mx1;
            float ms0 = mx0 * sc, ms1 = mx1 * sc;
            float rs0 = 0.f, rs1 = 0.f;
            uint32_t p[32];
#pragma unroll
            for (int j = 0; j < 16; j++) {
                float p0 = exp2f(sacc[j * 4 + 0] * sc - ms0);
                float p1 = exp2f(sacc[j * 4 + 1] * sc - ms0);
                float p2 = exp2f(sacc[j * 4 + 2] * sc - ms1);
                float p3 = exp2f(sacc[j * 4 + 3] * sc - ms1);
                rs0 += p0 + p1; rs1 += p2 + p3;
                p[j * 2 + 0] = pack_bf16(p0, p1);
                p[j * 2 + 1] = pack_bf16(p2, p3);
            }
            l0 = l0 * c0 + rs0; l1 = l1 * c1 + rs1;
#pragma unroll
            for (int j = 0; j < 16; j++) {
                o[j * 4 + 0] *= c0; o[j * 4 + 1] *= c0; o[j * 4 + 2] *= c1; o[j * 4 + 3] *= c1;
            }
            mbar_wait(bar_vf + 8 * s, ph);
            uint32_t vb = sV + s * A_TILE_BYTES;
            wgmma_fence();
#pragma unroll
            for (int kk = 0; kk < 8; kk++) {
                wgmma_m64n128k16_rs<1>(o, p[kk * 4 + 0], p[kk * 4 + 1], p[kk * 4 + 2], p[kk * 4 + 3],
                                       make_desc(vb + kk * 2048, 16384, 1024), 1);
            }
            wgmma_commit();
            wgmma_wait<0>();
            if (lane == 0) mbar_arrive(bar_ve + 8 * s);
        }
        l0 += __shfl_xor_sync(0xffffffffu, l0, 1);
        l0 += __shfl_xor_sync(0xffffffffu, l0, 2);
        l1 += __shfl_xor_sync(0xffffffffu, l1, 1);
        l1 += __shfl_xor_sync(0xffffffffu, l1, 2);
        float i0 = 1.f / l0, i1 = 1.f / l1;
        int r0 = qt * 128 + cw * 64 + warp * 16 + (lane >> 2);
        bf16* dst = g_o + (size_t)r0 * HD + head * DH + (lane & 3) * 2;
#pragma unroll
        for (int j = 0; j < 16; j++) {
            *reinterpret_cast<uint32_t*>(dst + j * 8) = pack_bf16(o[j * 4 + 0] * i0, o[j * 4 + 1] * i0);
            *reinterpret_cast<uint32_t*>(dst + (size_t)8 * HD + j * 8) = pack_bf16(o[j * 4 + 2] * i1, o[j * 4 + 3] * i1);
        }
    }
}

__global__ void __launch_bounds__(384, 1)
final_kernel(const __grid_constant__ CUtensorMap mapO, const __grid_constant__ CUtensorMap mapWo,
             const __grid_constant__ CUtensorMap mapH, const __grid_constant__ CUtensorMap mapW2,
             const bf16* __restrict__ x, const bf16* __restrict__ b2, bf16* __restrict__ out) {
    extern __shared__ uint8_t smem_raw[];
    uint32_t sbase = (smem_u32(smem_raw) + 1023) & ~1023u;
    uint32_t bar_full = sbase + G_STAGES * G_STAGE_BYTES;
    uint32_t bar_empty = bar_full + 8 * G_STAGES;
    int wg = threadIdx.x >> 7;
    int tid = threadIdx.x & 127;
    int m0 = blockIdx.y * 128, n0 = blockIdx.x * 128;
    constexpr int NK1 = HD / 64;
    constexpr int NK2 = (FF + 63) / 64;

    if (threadIdx.x == 0) {
        for (int i = 0; i < G_STAGES; i++) { mbar_init(bar_full + 8 * i, 1); mbar_init(bar_empty + 8 * i, 8); }
        fence_barrier_init();
    }
    __syncthreads();

    if (wg == 0) {
        reg_dealloc<40>();
        if (tid == 0) {
            for (int it = 0; it < NK1 + NK2; it++) {
                int s = it % G_STAGES;
                uint32_t ph = (it / G_STAGES) & 1;
                mbar_wait(bar_empty + 8 * s, ph ^ 1);
                mbar_expect_tx(bar_full + 8 * s, G_STAGE_BYTES);
                uint32_t a = sbase + s * G_STAGE_BYTES;
                const CUtensorMap* pa = it < NK1 ? &mapO : &mapH;
                const CUtensorMap* pb = it < NK1 ? &mapWo : &mapW2;
                int k = (it < NK1 ? it : it - NK1) * 64;
                tma_load_2d(a, pa, bar_full + 8 * s, k, m0);
                tma_load_2d(a + 16384, pb, bar_full + 8 * s, n0, k);
                tma_load_2d(a + 16384 + 8192, pb, bar_full + 8 * s, n0 + 64, k);
            }
        }
    } else {
        reg_alloc<232>();
        float acc[64], acc2[64];
#pragma unroll
        for (int i = 0; i < 64; i++) { acc[i] = 0.f; acc2[i] = 0.f; }
        int cw = wg - 1;
        for (int it = 0; it < NK1; it++) {
            int s = it % G_STAGES;
            uint32_t ph = (it / G_STAGES) & 1;
            mbar_wait(bar_full + 8 * s, ph);
            uint32_t a = sbase + s * G_STAGE_BYTES + cw * 8192;
            uint32_t b = sbase + s * G_STAGE_BYTES + 16384;
            wgmma_fence();
#pragma unroll
            for (int kk = 0; kk < 4; kk++)
                wgmma_m64n128k16_ss<0, 1>(acc, make_desc(a + kk * 32, 16, 1024), make_desc(b + kk * 2048, 8192, 1024), 1);
            wgmma_commit();
            wgmma_wait<0>();
            if ((tid & 31) == 0) mbar_arrive(bar_empty + 8 * s);
        }
        for (int it = NK1; it < NK1 + NK2; it++) {
            int s = it % G_STAGES;
            uint32_t ph = (it / G_STAGES) & 1;
            mbar_wait(bar_full + 8 * s, ph);
            uint32_t a = sbase + s * G_STAGE_BYTES + cw * 8192;
            uint32_t b = sbase + s * G_STAGE_BYTES + 16384;
            wgmma_fence();
#pragma unroll
            for (int kk = 0; kk < 4; kk++)
                wgmma_m64n128k16_ss<0, 1>(acc2, make_desc(a + kk * 32, 16, 1024), make_desc(b + kk * 2048, 8192, 1024), 1);
            wgmma_commit();
            wgmma_wait<0>();
            if ((tid & 31) == 0) mbar_arrive(bar_empty + 8 * s);
        }
        int warp = tid >> 5, lane = tid & 31;
        int r0 = m0 + cw * 64 + warp * 16 + (lane >> 2);
#pragma unroll
        for (int j = 0; j < 16; j++) {
            int c = n0 + j * 8 + (lane & 3) * 2;
            float b0 = __bfloat162float(b2[c]), b1 = __bfloat162float(b2[c + 1]);
#pragma unroll
            for (int h = 0; h < 2; h++) {
                int r = r0 + h * 8;
                float2 xv = __bfloat1622float2(*reinterpret_cast<const __nv_bfloat162*>(x + (size_t)r * DM + c));
                float g0 = acc2[j * 4 + h * 2 + 0] + b0, g1 = acc2[j * 4 + h * 2 + 1] + b1;
                g0 = g0 / (1.f + __expf(-g0)); g1 = g1 / (1.f + __expf(-g1));
                float o0 = xv.x + acc[j * 4 + h * 2 + 0] * g0;
                float o1 = xv.y + acc[j * 4 + h * 2 + 1] * g1;
                *reinterpret_cast<uint32_t*>(out + (size_t)r * DM + c) = pack_bf16(o0, o1);
            }
        }
    }
}

typedef CUresult (*EncodeFn)(CUtensorMap*, CUtensorMapDataType, cuuint32_t, void*, const cuuint64_t*, const cuuint64_t*,
                             const cuuint32_t*, const cuuint32_t*, CUtensorMapInterleave, CUtensorMapSwizzle,
                             CUtensorMapL2promotion, CUtensorMapFloatOOBfill);

static void make_map(EncodeFn fn, CUtensorMap* m, const void* ptr, uint64_t inner, uint64_t outer,
                     uint32_t box_inner, uint32_t box_outer) {
    cuuint64_t dims[2] = {inner, outer};
    cuuint64_t strides[1] = {inner * 2};
    cuuint32_t box[2] = {box_inner, box_outer};
    cuuint32_t es[2] = {1, 1};
    fn(m, CU_TENSOR_MAP_DATA_TYPE_BFLOAT16, 2, const_cast<void*>(ptr), dims, strides, box, es,
       CU_TENSOR_MAP_INTERLEAVE_NONE, CU_TENSOR_MAP_SWIZZLE_128B, CU_TENSOR_MAP_L2_PROMOTION_L2_256B,
       CU_TENSOR_MAP_FLOAT_OOB_FILL_NONE);
}

extern "C" void kernel_launch(void* const* d_in, const int* in_sizes, int n_in, void* d_out, int out_size) {
    const bf16* x  = (const bf16*)d_in[0];
    const bf16* kc = (const bf16*)d_in[1];
    const bf16* vc = (const bf16*)d_in[2];
    const bf16* wq = (const bf16*)d_in[3];
    const bf16* wo = (const bf16*)d_in[4];
    const bf16* w1 = (const bf16*)d_in[6];
    const bf16* b1 = (const bf16*)d_in[7];
    const bf16* w2 = (const bf16*)d_in[8];
    const bf16* b2 = (const bf16*)d_in[9];
    bf16* out = (bf16*)d_out;

    static bool inited = false;
    static CUtensorMap mXn, mY, mWq, mW1, mQ, mK, mV, mO, mWo, mH, mW2;
    static void *pq, *ph;
    if (!inited) {
        EncodeFn fn = nullptr;
        cudaDriverEntryPointQueryResult qres;
        cudaGetDriverEntryPoint("cuTensorMapEncodeTiled", (void**)&fn, cudaEnableDefault, &qres);
        void *pxn, *py, *po;
        cudaGetSymbolAddress(&pxn, g_xn); cudaGetSymbolAddress(&py, g_y); cudaGetSymbolAddress(&pq, g_q);
        cudaGetSymbolAddress(&ph, g_h); cudaGetSymbolAddress(&po, g_o);
        make_map(fn, &mXn, pxn, DM, SEQ, 64, 128);
        make_map(fn, &mY, py, DM, SEQ, 64, 128);
        make_map(fn, &mWq, wq, HD, DM, 64, 64);
        make_map(fn, &mW1, w1, FF, DM, 64, 64);
        make_map(fn, &mQ, pq, HD, SEQ, 64, 128);
        make_map(fn, &mK, kc, DH, NH * SEQ, 64, 128);
        make_map(fn, &mV, vc, DH, NH * SEQ, 64, 128);
        make_map(fn, &mO, po, HD, SEQ, 64, 128);
        make_map(fn, &mWo, wo, DM, HD, 64, 64);
        make_map(fn, &mH, ph, FF, SEQ, 64, 128);
        make_map(fn, &mW2, w2, DM, FF, 64, 64);
        cudaFuncSetAttribute(gemm_kernel<0>, cudaFuncAttributeMaxDynamicSharedMemorySize, G_SMEM);
        cudaFuncSetAttribute(gemm_kernel<1>, cudaFuncAttributeMaxDynamicSharedMemorySize, G_SMEM);
        cudaFuncSetAttribute(final_kernel, cudaFuncAttributeMaxDynamicSharedMemorySize, G_SMEM);
        cudaFuncSetAttribute(attn_kernel, cudaFuncAttributeMaxDynamicSharedMemorySize, A_SMEM);
        inited = true;
    }

    ln_kernel<<<SEQ / 8, 256>>>(x);
    gemm_kernel<0><<<dim3(HD / 128, SEQ / 128), 384, G_SMEM>>>(mXn, mWq, (bf16*)pq, HD, HD, DM, nullptr);
    gemm_kernel<1><<<dim3((FF + 127) / 128, SEQ / 128), 384, G_SMEM>>>(mY, mW1, (bf16*)ph, FF, FF, DM, b1);
    attn_kernel<<<dim3(SEQ / 128, NH), 384, A_SMEM>>>(mQ, mK, mV);
    final_kernel<<<dim3(DM / 128, SEQ / 128), 384, G_SMEM>>>(mO, mWo, mH, mW2, x, b2, out);
}
```

```cpp
#include <cuda_runtime.h>
#include <cuda_bf16.h>
#include <cuda.h>
#include <stdint.h>

typedef __nv_bfloat16 bf16;

constexpr int SEQ = 2048;
constexpr int DM  = 512;
constexpr int NH  = 32;
constexpr int DH  = 128;
constexpr int HD  = NH * DH;
constexpr int FF  = 1376;

__device__ bf16 g_xn[SEQ * DM];
__device__ bf16 g_y [SEQ * DM];
__device__ bf16 g_q [SEQ * HD];
__device__ bf16 g_h [SEQ * FF];
__device__ bf16 g_o [SEQ * HD];

__device__ __forceinline__ uint32_t smem_u32(const void* p) {
    return (uint32_t)__cvta_generic_to_shared(p);
}
__device__ __forceinline__ void mbar_init(uint32_t bar, uint32_t count) {
    asm volatile("mbarrier.init.shared::cta.b64 [%0], %1;" :: "r"(bar), "r"(count) : "memory");
}
__device__ __forceinline__ void mbar_arrive(uint32_t bar) {
    asm volatile("mbarrier.arrive.shared::cta.b64 _, [%0];" :: "r"(bar) : "memory");
}
__device__ __forceinline__ void mbar_expect_tx(uint32_t bar, uint32_t bytes) {
    asm volatile("mbarrier.arrive.expect_tx.shared::cta.b64 _, [%0], %1;" :: "r"(bar), "r"(bytes) : "memory");
}
__device__ __forceinline__ void mbar_wait(uint32_t bar, uint32_t parity) {
    asm volatile(
        "{\n"
        ".reg .pred p;\n"
        "LAB_WAIT:\n"
        "mbarrier.try_wait.parity.shared::cta.b64 p, [%0], %1;\n"
        "@p bra DONE;\n"
        "bra LAB_WAIT;\n"
        "DONE:\n"
        "}\n" :: "r"(bar), "r"(parity) : "memory");
}
__device__ __forceinline__ void tma_load_2d(uint32_t dst, const CUtensorMap* map, uint32_t bar, int c0, int c1) {
    asm volatile(
        "cp.async.bulk.tensor.2d.shared::cluster.global.mbarrier::complete_tx::bytes [%0], [%1, {%3, %4}], [%2];"
        :: "r"(dst), "l"((uint64_t)map), "r"(bar), "r"(c0), "r"(c1) : "memory");
}
__device__ __forceinline__ void wgmma_fence() { asm volatile("wgmma.fence.sync.aligned;" ::: "memory"); }
__device__ __forceinline__ void wgmma_commit() { asm volatile("wgmma.commit_group.sync.aligned;" ::: "memory"); }
template <int N> __device__ __forceinline__ void wgmma_wait() {
    asm volatile("wgmma.wait_group.sync.aligned %0;" :: "n"(N) : "memory");
}
template <int R> __device__ __forceinline__ void reg_alloc() {
    asm volatile("setmaxnreg.inc.sync.aligned.u32 %0;" :: "n"(R));
}
template <int R> __device__ __forceinline__ void reg_dealloc() {
    asm volatile("setmaxnreg.dec.sync.aligned.u32 %0;" :: "n"(R));
}
__device__ __forceinline__ void fence_barrier_init() {
    asm volatile("fence.mbarrier_init.release.cluster;" ::: "memory");
}
__device__ __forceinline__ void fence_proxy_async() {
    asm volatile("fence.proxy.async.shared::cta;" ::: "memory");
}

__device__ __forceinline__ void named_sync(int id, int n) {
    asm volatile("bar.sync %0, %1;" :: "r"(id), "r"(n) : "memory");
}
__device__ __forceinline__ void named_arrive(int id, int n) {
    asm volatile("bar.arrive %0, %1;" :: "r"(id), "r"(n) : "memory");
}
__device__ __forceinline__ float fast_exp2(float x) {
    float y;
    asm("ex2.approx.ftz.f32 %0, %1;" : "=f"(y) : "f"(x));
    return y;
}

__device__ __forceinline__ uint64_t make_desc(uint32_t addr, uint32_t lbo_bytes, uint32_t sbo_bytes) {
    uint64_t d = 0;
    d |= (uint64_t)((addr & 0x3FFFF) >> 4);
    d |= (uint64_t)((lbo_bytes & 0x3FFFF) >> 4) << 16;
    d |= (uint64_t)((sbo_bytes & 0x3FFFF) >> 4) << 32;
    d |= (uint64_t)1 << 62;
    return d;
}

template <int TA, int TB>
__device__ __forceinline__ void wgmma_m64n128k16_ss(float (&d)[64], uint64_t da, uint64_t db, int scale_d) {
    asm volatile(
        "{\n.reg .pred p;\nsetp.ne.b32 p, %66, 0;\n"
        "wgmma.mma_async.sync.aligned.m64n128k16.f32.bf16.bf16 "
        "{%0,%1,%2,%3,%4,%5,%6,%7,%8,%9,%10,%11,%12,%13,%14,%15,"
        "%16,%17,%18,%19,%20,%21,%22,%23,%24,%25,%26,%27,%28,%29,%30,%31,"
        "%32,%33,%34,%35,%36,%37,%38,%39,%40,%41,%42,%43,%44,%45,%46,%47,"
        "%48,%49,%50,%51,%52,%53,%54,%55,%56,%57,%58,%59,%60,%61,%62,%63},"
        " %64, %65, p, 1, 1, %67, %68;\n}\n"
        : "+f"(d[0]), "+f"(d[1]), "+f"(d[2]), "+f"(d[3]), "+f"(d[4]), "+f"(d[5]), "+f"(d[6]), "+f"(d[7]),
          "+f"(d[8]), "+f"(d[9]), "+f"(d[10]), "+f"(d[11]), "+f"(d[12]), "+f"(d[13]), "+f"(d[14]), "+f"(d[15]),
          "+f"(d[16]), "+f"(d[17]), "+f"(d[18]), "+f"(d[19]), "+f"(d[20]), "+f"(d[21]), "+f"(d[22]), "+f"(d[23]),
          "+f"(d[24]), "+f"(d[25]), "+f"(d[26]), "+f"(d[27]), "+f"(d[28]), "+f"(d[29]), "+f"(d[30]), "+f"(d[31]),
          "+f"(d[32]), "+f"(d[33]), "+f"(d[34]), "+f"(d[35]), "+f"(d[36]), "+f"(d[37]), "+f"(d[38]), "+f"(d[39]),
          "+f"(d[40]), "+f"(d[41]), "+f"(d[42]), "+f"(d[43]), "+f"(d[44]), "+f"(d[45]), "+f"(d[46]), "+f"(d[47]),
          "+f"(d[48]), "+f"(d[49]), "+f"(d[50]), "+f"(d[51]), "+f"(d[52]), "+f"(d[53]), "+f"(d[54]), "+f"(d[55]),
          "+f"(d[56]), "+f"(d[57]), "+f"(d[58]), "+f"(d[59]), "+f"(d[60]), "+f"(d[61]), "+f"(d[62]), "+f"(d[63])
        : "l"(da), "l"(db), "r"(scale_d), "n"(TA), "n"(TB));
}

template <int TB>
__device__ __forceinline__ void wgmma_m64n128k16_rs(float (&d)[64], uint32_t a0, uint32_t a1, uint32_t a2, uint32_t a3,
                                                    uint64_t db, int scale_d) {
    asm volatile(
        "{\n.reg .pred p;\nsetp.ne.b32 p, %69, 0;\n"
        "wgmma.mma_async.sync.aligned.m64n128k16.f32.bf16.bf16 "
        "{%0,%1,%2,%3,%4,%5,%6,%7,%8,%9,%10,%11,%12,%13,%14,%15,"
        "%16,%17,%18,%19,%20,%21,%22,%23,%24,%25,%26,%27,%28,%29,%30,%31,"
        "%32,%33,%34,%35,%36,%37,%38,%39,%40,%41,%42,%43,%44,%45,%46,%47,"
        "%48,%49,%50,%51,%52,%53,%54,%55,%56,%57,%58,%59,%60,%61,%62,%63},"
        " {%64,%65,%66,%67}, %68, p, 1, 1, %70;\n}\n"
        : "+f"(d[0]), "+f"(d[1]), "+f"(d[2]), "+f"(d[3]), "+f"(d[4]), "+f"(d[5]), "+f"(d[6]), "+f"(d[7]),
          "+f"(d[8]), "+f"(d[9]), "+f"(d[10]), "+f"(d[11]), "+f"(d[12]), "+f"(d[13]), "+f"(d[14]), "+f"(d[15]),
          "+f"(d[16]), "+f"(d[17]), "+f"(d[18]), "+f"(d[19]), "+f"(d[20]), "+f"(d[21]), "+f"(d[22]), "+f"(d[23]),
          "+f"(d[24]), "+f"(d[25]), "+f"(d[26]), "+f"(d[27]), "+f"(d[28]), "+f"(d[29]), "+f"(d[30]), "+f"(d[31]),
          "+f"(d[32]), "+f"(d[33]), "+f"(d[34]), "+f"(d[35]), "+f"(d[36]), "+f"(d[37]), "+f"(d[38]), "+f"(d[39]),
          "+f"(d[40]), "+f"(d[41]), "+f"(d[42]), "+f"(d[43]), "+f"(d[44]), "+f"(d[45]), "+f"(d[46]), "+f"(d[47]),
          "+f"(d[48]), "+f"(d[49]), "+f"(d[50]), "+f"(d[51]), "+f"(d[52]), "+f"(d[53]), "+f"(d[54]), "+f"(d[55]),
          "+f"(d[56]), "+f"(d[57]), "+f"(d[58]), "+f"(d[59]), "+f"(d[60]), "+f"(d[61]), "+f"(d[62]), "+f"(d[63])
        : "r"(a0), "r"(a1), "r"(a2), "r"(a3), "l"(db), "r"(scale_d), "n"(TB));
}

__device__ __forceinline__ uint32_t pack_bf16(float lo, float hi) {
    __nv_bfloat162 v = __floats2bfloat162_rn(lo, hi);
    return *reinterpret_cast<uint32_t*>(&v);
}

__global__ void __launch_bounds__(256) ln_kernel(const bf16* __restrict__ x) {
    int warp = threadIdx.x >> 5, lane = threadIdx.x & 31;
    int row = blockIdx.x * 8 + warp;
    const uint4* src = reinterpret_cast<const uint4*>(x + (size_t)row * DM);
    float v[16];
#pragma unroll
    for (int i = 0; i < 2; i++) {
        uint4 u = src[lane + i * 32];
        const __nv_bfloat162* h = reinterpret_cast<const __nv_bfloat162*>(&u);
#pragma unroll
        for (int j = 0; j < 4; j++) {
            float2 f = __bfloat1622float2(h[j]);
            v[i * 8 + j * 2] = f.x; v[i * 8 + j * 2 + 1] = f.y;
        }
    }
#pragma unroll
    for (int pass = 0; pass < 2; pass++) {
        float s = 0.f;
#pragma unroll
        for (int i = 0; i < 16; i++) s += v[i];
#pragma unroll
        for (int o = 16; o > 0; o >>= 1) s += __shfl_xor_sync(0xffffffffu, s, o);
        float mean = s * (1.f / DM);
        float q = 0.f;
#pragma unroll
        for (int i = 0; i < 16; i++) { float d = v[i] - mean; q += d * d; }
#pragma unroll
        for (int o = 16; o > 0; o >>= 1) q += __shfl_xor_sync(0xffffffffu, q, o);
        float rstd = 1.0f / sqrtf(q * (1.f / DM) + 1e-5f);
        bf16* dst = (pass == 0 ? g_xn : g_y) + (size_t)row * DM;
#pragma unroll
        for (int i = 0; i < 2; i++) {
            uint4 u;
            uint32_t* w = reinterpret_cast<uint32_t*>(&u);
#pragma unroll
            for (int j = 0; j < 4; j++) {
                __nv_bfloat162 h = __floats2bfloat162_rn((v[i * 8 + j * 2] - mean) * rstd, (v[i * 8 + j * 2 + 1] - mean) * rstd);
                w[j] = *reinterpret_cast<uint32_t*>(&h);
                float2 f = __bfloat1622float2(h);
                v[i * 8 + j * 2] = f.x; v[i * 8 + j * 2 + 1] = f.y;
            }
            reinterpret_cast<uint4*>(dst)[lane + i * 32] = u;
        }
    }
}

constexpr int G_STAGES = 4;
constexpr int G_STAGE_BYTES = 32768;
constexpr int G_SMEM = G_STAGES * G_STAGE_BYTES + 1024 + 256;

__device__ __forceinline__ float gelu_tanh(float x) {
    float u = 0.7978845608028654f * (x + 0.044715f * x * x * x);
    float t = 1.f - 2.f / (1.f + __expf(2.f * u));
    return 0.5f * x * (1.f + t);
}

template <int MODE>
__global__ void __launch_bounds__(384, 1)
gemm_kernel(const __grid_constant__ CUtensorMap mapA, const __grid_constant__ CUtensorMap mapB,
            bf16* __restrict__ C, int ldc, int N, int K, const bf16* __restrict__ bias) {
    extern __shared__ uint8_t smem_raw[];
    uint32_t sbase = (smem_u32(smem_raw) + 1023) & ~1023u;
    uint32_t bar_full = sbase + G_STAGES * G_STAGE_BYTES;
    uint32_t bar_empty = bar_full + 8 * G_STAGES;
    int wg = threadIdx.x >> 7;
    int tid = threadIdx.x & 127;
    int m0 = blockIdx.y * 128, n0 = blockIdx.x * 128;
    int nk = K / 64;

    if (threadIdx.x == 0) {
        for (int i = 0; i < G_STAGES; i++) { mbar_init(bar_full + 8 * i, 1); mbar_init(bar_empty + 8 * i, 8); }
        fence_barrier_init();
    }
    __syncthreads();

    if (wg == 0) {
        reg_dealloc<40>();
        if (tid == 0) {
            for (int it = 0; it < nk; it++) {
                int s = it % G_STAGES;
                uint32_t ph = (it / G_STAGES) & 1;
                mbar_wait(bar_empty + 8 * s, ph ^ 1);
                mbar_expect_tx(bar_full + 8 * s, G_STAGE_BYTES);
                uint32_t a = sbase + s * G_STAGE_BYTES;
                tma_load_2d(a, &mapA, bar_full + 8 * s, it * 64, m0);
                tma_load_2d(a + 16384, &mapB, bar_full + 8 * s, n0, it * 64);
                tma_load_2d(a + 16384 + 8192, &mapB, bar_full + 8 * s, n0 + 64, it * 64);
            }
        }
    } else {
        reg_alloc<232>();
        float acc[64];
#pragma unroll
        for (int i = 0; i < 64; i++) acc[i] = 0.f;
        int cw = wg - 1;
        for (int it = 0; it < nk; it++) {
            int s = it % G_STAGES;
            uint32_t ph = (it / G_STAGES) & 1;
            mbar_wait(bar_full + 8 * s, ph);
            uint32_t a = sbase + s * G_STAGE_BYTES + cw * 8192;
            uint32_t b = sbase + s * G_STAGE_BYTES + 16384;
            wgmma_fence();
#pragma unroll
            for (int kk = 0; kk < 4; kk++) {
                wgmma_m64n128k16_ss<0, 1>(acc, make_desc(a + kk * 32, 16, 1024), make_desc(b + kk * 2048, 8192, 1024), 1);
            }
            wgmma_commit();
            wgmma_wait<0>();
            if ((tid & 31) == 0) mbar_arrive(bar_empty + 8 * s);
        }
        int warp = tid >> 5, lane = tid & 31;
        int r0 = m0 + cw * 64 + warp * 16 + (lane >> 2);
#pragma unroll
        for (int j = 0; j < 16; j++) {
            int c = n0 + j * 8 + (lane & 3) * 2;
            if (c < N) {
                float v0 = acc[j * 4 + 0], v1 = acc[j * 4 + 1], v2 = acc[j * 4 + 2], v3 = acc[j * 4 + 3];
                if (MODE == 1) {
                    float b0 = __bfloat162float(bias[c]), b1 = __bfloat162float(bias[c + 1]);
                    v0 = gelu_tanh(v0 + b0); v1 = gelu_tanh(v1 + b1);
                    v2 = gelu_tanh(v2 + b0); v3 = gelu_tanh(v3 + b1);
                }
                *reinterpret_cast<uint32_t*>(C + (size_t)r0 * ldc + c) = pack_bf16(v0, v1);
                *reinterpret_cast<uint32_t*>(C + (size_t)(r0 + 8) * ldc + c) = pack_bf16(v2, v3);
            }
        }
    }
}

constexpr int A_KV_STAGES = 2;
constexpr int A_TILE_BYTES = 128 * 128 * 2;
constexpr int A_SMEM = A_TILE_BYTES * (1 + 2 * A_KV_STAGES) + 1024 + 256;

__global__ void __launch_bounds__(384, 1)
attn_kernel(const __grid_constant__ CUtensorMap mapQ, const __grid_constant__ CUtensorMap mapK,
            const __grid_constant__ CUtensorMap mapV) {
    extern __shared__ uint8_t smem_raw[];
    uint32_t sbase = (smem_u32(smem_raw) + 1023) & ~1023u;
    uint32_t sQ = sbase;
    uint32_t sK = sQ + A_TILE_BYTES;
    uint32_t sV = sK + A_KV_STAGES * A_TILE_BYTES;
    uint32_t bars = sV + A_KV_STAGES * A_TILE_BYTES;
    uint32_t bar_q = bars;
    uint32_t bar_kf = bars + 8, bar_ke = bar_kf + 8 * A_KV_STAGES;
    uint32_t bar_vf = bar_ke + 8 * A_KV_STAGES, bar_ve = bar_vf + 8 * A_KV_STAGES;
    int wg = threadIdx.x >> 7;
    int tid = threadIdx.x & 127;
    int qt = blockIdx.x, head = blockIdx.y;
    constexpr int NT = SEQ / 128;

    if (threadIdx.x == 0) {
        mbar_init(bar_q, 1);
        for (int i = 0; i < A_KV_STAGES; i++) {
            mbar_init(bar_kf + 8 * i, 1); mbar_init(bar_ke + 8 * i, 8);
            mbar_init(bar_vf + 8 * i, 1); mbar_init(bar_ve + 8 * i, 8);
        }
        fence_barrier_init();
    }
    __syncthreads();

    if (wg == 0) {
        reg_dealloc<40>();
        if (tid == 0) {
            mbar_expect_tx(bar_q, A_TILE_BYTES);
            tma_load_2d(sQ, &mapQ, bar_q, head * DH, qt * 128);
            tma_load_2d(sQ + 16384, &mapQ, bar_q, head * DH + 64, qt * 128);
            for (int it = 0; it < NT; it++) {
                int s = it % A_KV_STAGES;
                uint32_t ph = (it / A_KV_STAGES) & 1;
                int row = head * SEQ + it * 128;
                mbar_wait(bar_ke + 8 * s, ph ^ 1);
                mbar_expect_tx(bar_kf + 8 * s, A_TILE_BYTES);
                tma_load_2d(sK + s * A_TILE_BYTES, &mapK, bar_kf + 8 * s, 0, row);
                tma_load_2d(sK + s * A_TILE_BYTES + 16384, &mapK, bar_kf + 8 * s, 64, row);
                mbar_wait(bar_ve + 8 * s, ph ^ 1);
                mbar_expect_tx(bar_vf + 8 * s, A_TILE_BYTES);
                tma_load_2d(sV + s * A_TILE_BYTES, &mapV, bar_vf + 8 * s, 0, row);
                tma_load_2d(sV + s * A_TILE_BYTES + 16384, &mapV, bar_vf + 8 * s, 64, row);
            }
        }
    } else {
        reg_alloc<232>();
        int cw = wg - 1;
        int warp = tid >> 5, lane = tid & 31;
        float o[64];
#pragma unroll
        for (int i = 0; i < 64; i++) o[i] = 0.f;
        float m0 = -INFINITY, m1 = -INFINITY, l0 = 0.f, l1 = 0.f;
        const float sc = 0.08838834764831845f * 1.4426950408889634f;
        if (cw == 1) named_arrive(1, 256);
        mbar_wait(bar_q, 0);
        uint32_t qa = sQ + cw * 8192;
        float sacc[64];
        uint32_t p[32];
        mbar_wait(bar_kf, 0);
        named_sync(1 + cw, 256);
        wgmma_fence();
#pragma unroll
        for (int kk = 0; kk < 8; kk++) {
            uint32_t off = (kk >> 2) * 16384 + (kk & 3) * 32;
            wgmma_m64n128k16_ss<0, 0>(sacc, make_desc(qa + off, 16, 1024), make_desc(sK + off, 16, 1024), kk != 0);
        }
        wgmma_commit();
        named_arrive(1 + (cw ^ 1), 256);
        wgmma_wait<0>();
        if (lane == 0) mbar_arrive(bar_ke);
        {
            float mx0 = -INFINITY, mx1 = -INFINITY;
#pragma unroll
            for (int j = 0; j < 16; j++) {
                mx0 = fmaxf(mx0, fmaxf(sacc[j * 4 + 0], sacc[j * 4 + 1]));
                mx1 = fmaxf(mx1, fmaxf(sacc[j * 4 + 2], sacc[j * 4 + 3]));
            }
            mx0 = fmaxf(mx0, __shfl_xor_sync(0xffffffffu, mx0, 1));
            mx0 = fmaxf(mx0, __shfl_xor_sync(0xffffffffu, mx0, 2));
            mx1 = fmaxf(mx1, __shfl_xor_sync(0xffffffffu, mx1, 1));
            mx1 = fmaxf(mx1, __shfl_xor_sync(0xffffffffu, mx1, 2));
            m0 = mx0; m1 = mx1;
            float ms0 = mx0 * sc, ms1 = mx1 * sc;
#pragma unroll
            for (int j = 0; j < 16; j++) {
                float p0 = fast_exp2(sacc[j * 4 + 0] * sc - ms0);
                float p1 = fast_exp2(sacc[j * 4 + 1] * sc - ms0);
                float p2 = fast_exp2(sacc[j * 4 + 2] * sc - ms1);
                float p3 = fast_exp2(sacc[j * 4 + 3] * sc - ms1);
                l0 += p0 + p1; l1 += p2 + p3;
                p[j * 2 + 0] = pack_bf16(p0, p1);
                p[j * 2 + 1] = pack_bf16(p2, p3);
            }
        }
        for (int it = 1; it < NT; it++) {
            int s = it % A_KV_STAGES;
            uint32_t ph = (it / A_KV_STAGES) & 1;
            int sp = (it - 1) % A_KV_STAGES;
            uint32_t php = ((it - 1) / A_KV_STAGES) & 1;
            mbar_wait(bar_kf + 8 * s, ph);
            named_sync(1 + cw, 256);
            uint32_t kb = sK + s * A_TILE_BYTES;
            wgmma_fence();
#pragma unroll
            for (int kk = 0; kk < 8; kk++) {
                uint32_t off = (kk >> 2) * 16384 + (kk & 3) * 32;
                wgmma_m64n128k16_ss<0, 0>(sacc, make_desc(qa + off, 16, 1024), make_desc(kb + off, 16, 1024), kk != 0);
            }
            wgmma_commit();
            mbar_wait(bar_vf + 8 * sp, php);
            uint32_t vb = sV + sp * A_TILE_BYTES;
#pragma unroll
            for (int kk = 0; kk < 8; kk++) {
                wgmma_m64n128k16_rs<1>(o, p[kk * 4 + 0], p[kk * 4 + 1], p[kk * 4 + 2], p[kk * 4 + 3],
                                       make_desc(vb + kk * 2048, 16384, 1024), 1);
            }
            wgmma_commit();
            named_arrive(1 + (cw ^ 1), 256);
            wgmma_wait<1>();
            if (lane == 0) mbar_arrive(bar_ke + 8 * s);
            float mx0 = m0, mx1 = m1;
#pragma unroll
            for (int j = 0; j < 16; j++) {
                mx0 = fmaxf(mx0, fmaxf(sacc[j * 4 + 0], sacc[j * 4 + 1]));
                mx1 = fmaxf(mx1, fmaxf(sacc[j * 4 + 2], sacc[j * 4 + 3]));
            }
            mx0 = fmaxf(mx0, __shfl_xor_sync(0xffffffffu, mx0, 1));
            mx0 = fmaxf(mx0, __shfl_xor_sync(0xffffffffu, mx0, 2));
            mx1 = fmaxf(mx1, __shfl_xor_sync(0xffffffffu, mx1, 1));
            mx1 = fmaxf(mx1, __shfl_xor_sync(0xffffffffu, mx1, 2));
            float c0 = fast_exp2((m0 - mx0) * sc), c1 = fast_exp2((m1 - mx1) * sc);
            m0 = mx0; m1 = mx1;
            float ms0 = mx0 * sc, ms1 = mx1 * sc;
            float rs0 = 0.f, rs1 = 0.f;
#pragma unroll
            for (int j = 0; j < 16; j++) {
                sacc[j * 4 + 0] = fast_exp2(sacc[j * 4 + 0] * sc - ms0);
                sacc[j * 4 + 1] = fast_exp2(sacc[j * 4 + 1] * sc - ms0);
                sacc[j * 4 + 2] = fast_exp2(sacc[j * 4 + 2] * sc - ms1);
                sacc[j * 4 + 3] = fast_exp2(sacc[j * 4 + 3] * sc - ms1);
                rs0 += sacc[j * 4 + 0] + sacc[j * 4 + 1]; rs1 += sacc[j * 4 + 2] + sacc[j * 4 + 3];
            }
            l0 = l0 * c0 + rs0; l1 = l1 * c1 + rs1;
            wgmma_wait<0>();
            if (lane == 0) mbar_arrive(bar_ve + 8 * sp);
#pragma unroll
            for (int j = 0; j < 16; j++) {
                o[j * 4 + 0] *= c0; o[j * 4 + 1] *= c0; o[j * 4 + 2] *= c1; o[j * 4 + 3] *= c1;
                p[j * 2 + 0] = pack_bf16(sacc[j * 4 + 0], sacc[j * 4 + 1]);
                p[j * 2 + 1] = pack_bf16(sacc[j * 4 + 2], sacc[j * 4 + 3]);
            }
        }
        {
            int sp = (NT - 1) % A_KV_STAGES;
            uint32_t php = ((NT - 1) / A_KV_STAGES) & 1;
            mbar_wait(bar_vf + 8 * sp, php);
            uint32_t vb = sV + sp * A_TILE_BYTES;
            wgmma_fence();
#pragma unroll
            for (int kk = 0; kk < 8; kk++) {
                wgmma_m64n128k16_rs<1>(o, p[kk * 4 + 0], p[kk * 4 + 1], p[kk * 4 + 2], p[kk * 4 + 3],
                                       make_desc(vb + kk * 2048, 16384, 1024), 1);
            }
            wgmma_commit();
            wgmma_wait<0>();
        }
        l0 += __shfl_xor_sync(0xffffffffu, l0, 1);
        l0 += __shfl_xor_sync(0xffffffffu, l0, 2);
        l1 += __shfl_xor_sync(0xffffffffu, l1, 1);
        l1 += __shfl_xor_sync(0xffffffffu, l1, 2);
        float i0 = 1.f / l0, i1 = 1.f / l1;
        int r0 = qt * 128 + cw * 64 + warp * 16 + (lane >> 2);
        bf16* dst = g_o + (size_t)r0 * HD + head * DH + (lane & 3) * 2;
#pragma unroll
        for (int j = 0; j < 16; j++) {
            *reinterpret_cast<uint32_t*>(dst + j * 8) = pack_bf16(o[j * 4 + 0] * i0, o[j * 4 + 1] * i0);
            *reinterpret_cast<uint32_t*>(dst + (size_t)8 * HD + j * 8) = pack_bf16(o[j * 4 + 2] * i1, o[j * 4 + 3] * i1);
        }
    }
}

__global__ void __launch_bounds__(384, 1)
final_kernel(const __grid_constant__ CUtensorMap mapO, const __grid_constant__ CUtensorMap mapWo,
             const __grid_constant__ CUtensorMap mapH, const __grid_constant__ CUtensorMap mapW2,
             const bf16* __restrict__ x, const bf16* __restrict__ b2, bf16* __restrict__ out) {
    extern __shared__ uint8_t smem_raw[];
    uint32_t sbase = (smem_u32(smem_raw) + 1023) & ~1023u;
    uint32_t bar_full = sbase + G_STAGES * G_STAGE_BYTES;
    uint32_t bar_empty = bar_full + 8 * G_STAGES;
    int wg = threadIdx.x >> 7;
    int tid = threadIdx.x & 127;
    int m0 = blockIdx.y * 128, n0 = blockIdx.x * 128;
    constexpr int NK1 = HD / 64;
    constexpr int NK2 = (FF + 63) / 64;

    if (threadIdx.x == 0) {
        for (int i = 0; i < G_STAGES; i++) { mbar_init(bar_full + 8 * i, 1); mbar_init(bar_empty + 8 * i, 8); }
        fence_barrier_init();
    }
    __syncthreads();

    if (wg == 0) {
        reg_dealloc<40>();
        if (tid == 0) {
            for (int it = 0; it < NK1 + NK2; it++) {
                int s = it % G_STAGES;
                uint32_t ph = (it / G_STAGES) & 1;
                mbar_wait(bar_empty + 8 * s, ph ^ 1);
                mbar_expect_tx(bar_full + 8 * s, G_STAGE_BYTES);
                uint32_t a = sbase + s * G_STAGE_BYTES;
                const CUtensorMap* pa = it < NK1 ? &mapO : &mapH;
                const CUtensorMap* pb = it < NK1 ? &mapWo : &mapW2;
                int k = (it < NK1 ? it : it - NK1) * 64;
                tma_load_2d(a, pa, bar_full + 8 * s, k, m0);
                tma_load_2d(a + 16384, pb, bar_full + 8 * s, n0, k);
                tma_load_2d(a + 16384 + 8192, pb, bar_full + 8 * s, n0 + 64, k);
            }
        }
    } else {
        reg_alloc<232>();
        float acc[64], acc2[64];
#pragma unroll
        for (int i = 0; i < 64; i++) { acc[i] = 0.f; acc2[i] = 0.f; }
        int cw = wg - 1;
        for (int it = 0; it < NK1; it++) {
            int s = it % G_STAGES;
            uint32_t ph = (it / G_STAGES) & 1;
            mbar_wait(bar_full + 8 * s, ph);
            uint32_t a = sbase + s * G_STAGE_BYTES + cw * 8192;
            uint32_t b = sbase + s * G_STAGE_BYTES + 16384;
            wgmma_fence();
#pragma unroll
            for (int kk = 0; kk < 4; kk++)
                wgmma_m64n128k16_ss<0, 1>(acc, make_desc(a + kk * 32, 16, 1024), make_desc(b + kk * 2048, 8192, 1024), 1);
            wgmma_commit();
            wgmma_wait<0>();
            if ((tid & 31) == 0) mbar_arrive(bar_empty + 8 * s);
        }
        for (int it = NK1; it < NK1 + NK2; it++) {
            int s = it % G_STAGES;
            uint32_t ph = (it / G_STAGES) & 1;
            mbar_wait(bar_full + 8 * s, ph);
            uint32_t a = sbase + s * G_STAGE_BYTES + cw * 8192;
            uint32_t b = sbase + s * G_STAGE_BYTES + 16384;
            wgmma_fence();
#pragma unroll
            for (int kk = 0; kk < 4; kk++)
                wgmma_m64n128k16_ss<0, 1>(acc2, make_desc(a + kk * 32, 16, 1024), make_desc(b + kk * 2048, 8192, 1024), 1);
            wgmma_commit();
            wgmma_wait<0>();
            if ((tid & 31) == 0) mbar_arrive(bar_empty + 8 * s);
        }
        int warp = tid >> 5, lane = tid & 31;
        int r0 = m0 + cw * 64 + warp * 16 + (lane >> 2);
#pragma unroll
        for (int j = 0; j < 16; j++) {
            int c = n0 + j * 8 + (lane & 3) * 2;
            float b0 = __bfloat162float(b2[c]), b1 = __bfloat162float(b2[c + 1]);
#pragma unroll
            for (int h = 0; h < 2; h++) {
                int r = r0 + h * 8;
                float2 xv = __bfloat1622float2(*reinterpret_cast<const __nv_bfloat162*>(x + (size_t)r * DM + c));
                float g0 = acc2[j * 4 + h * 2 + 0] + b0, g1 = acc2[j * 4 + h * 2 + 1] + b1;
                g0 = g0 / (1.f + __expf(-g0)); g1 = g1 / (1.f + __expf(-g1));
                float o0 = xv.x + acc[j * 4 + h * 2 + 0] * g0;
                float o1 = xv.y + acc[j * 4 + h * 2 + 1] * g1;
                *reinterpret_cast<uint32_t*>(out + (size_t)r * DM + c) = pack_bf16(o0, o1);
            }
        }
    }
}

typedef CUresult (*EncodeFn)(CUtensorMap*, CUtensorMapDataType, cuuint32_t, void*, const cuuint64_t*, const cuuint64_t*,
                             const cuuint32_t*, const cuuint32_t*, CUtensorMapInterleave, CUtensorMapSwizzle,
                             CUtensorMapL2promotion, CUtensorMapFloatOOBfill);

static void make_map(EncodeFn fn, CUtensorMap* m, const void* ptr, uint64_t inner, uint64_t outer,
                     uint32_t box_inner, uint32_t box_outer) {
    cuuint64_t dims[2] = {inner, outer};
    cuuint64_t strides[1] = {inner * 2};
    cuuint32_t box[2] = {box_inner, box_outer};
    cuuint32_t es[2] = {1, 1};
    fn(m, CU_TENSOR_MAP_DATA_TYPE_BFLOAT16, 2, const_cast<void*>(ptr), dims, strides, box, es,
       CU_TENSOR_MAP_INTERLEAVE_NONE, CU_TENSOR_MAP_SWIZZLE_128B, CU_TENSOR_MAP_L2_PROMOTION_L2_256B,
       CU_TENSOR_MAP_FLOAT_OOB_FILL_NONE);
}

extern "C" void kernel_launch(void* const* d_in, const int* in_sizes, int n_in, void* d_out, int out_size) {
    const bf16* x  = (const bf16*)d_in[0];
    const bf16* kc = (const bf16*)d_in[1];
    const bf16* vc = (const bf16*)d_in[2];
    const bf16* wq = (const bf16*)d_in[3];
    const bf16* wo = (const bf16*)d_in[4];
    const bf16* w1 = (const bf16*)d_in[6];
    const bf16* b1 = (const bf16*)d_in[7];
    const bf16* w2 = (const bf16*)d_in[8];
    const bf16* b2 = (const bf16*)d_in[9];
    bf16* out = (bf16*)d_out;

    static bool inited = false;
    static CUtensorMap mXn, mY, mWq, mW1, mQ, mK, mV, mO, mWo, mH, mW2;
    static void *pq, *ph;
    if (!inited) {
        EncodeFn fn = nullptr;
        cudaDriverEntryPointQueryResult qres;
        cudaGetDriverEntryPoint("cuTensorMapEncodeTiled", (void**)&fn, cudaEnableDefault, &qres);
        void *pxn, *py, *po;
        cudaGetSymbolAddress(&pxn, g_xn); cudaGetSymbolAddress(&py, g_y); cudaGetSymbolAddress(&pq, g_q);
        cudaGetSymbolAddress(&ph, g_h); cudaGetSymbolAddress(&po, g_o);
        make_map(fn, &mXn, pxn, DM, SEQ, 64, 128);
        make_map(fn, &mY, py, DM, SEQ, 64, 128);
        make_map(fn, &mWq, wq, HD, DM, 64, 64);
        make_map(fn, &mW1, w1, FF, DM, 64, 64);
        make_map(fn, &mQ, pq, HD, SEQ, 64, 128);
        make_map(fn, &mK, kc, DH, NH * SEQ, 64, 128);
        make_map(fn, &mV, vc, DH, NH * SEQ, 64, 128);
        make_map(fn, &mO, po, HD, SEQ, 64, 128);
        make_map(fn, &mWo, wo, DM, HD, 64, 64);
        make_map(fn, &mH, ph, FF, SEQ, 64, 128);
        make_map(fn, &mW2, w2, DM, FF, 64, 64);
        cudaFuncSetAttribute(gemm_kernel<0>, cudaFuncAttributeMaxDynamicSharedMemorySize, G_SMEM);
        cudaFuncSetAttribute(gemm_kernel<1>, cudaFuncAttributeMaxDynamicSharedMemorySize, G_SMEM);
        cudaFuncSetAttribute(final_kernel, cudaFuncAttributeMaxDynamicSharedMemorySize, G_SMEM);
        cudaFuncSetAttribute(attn_kernel, cudaFuncAttributeMaxDynamicSharedMemorySize, A_SMEM);
        inited = true;
    }

    ln_kernel<<<SEQ / 8, 256>>>(x);
    gemm_kernel<0><<<dim3(HD / 128, SEQ / 128), 384, G_SMEM>>>(mXn, mWq, (bf16*)pq, HD, HD, DM, nullptr);
    gemm_kernel<1><<<dim3((FF + 127) / 128, SEQ / 128), 384, G_SMEM>>>(mY, mW1, (bf16*)ph, FF, FF, DM, b1);
    attn_kernel<<<dim3(SEQ / 128, NH), 384, A_SMEM>>>(mQ, mK, mV);
    final_kernel<<<dim3(DM / 128, SEQ / 128), 384, G_SMEM>>>(mO, mWo, mH, mW2, x, b2, out);
}
```

```cpp
#include <cuda_runtime.h>
#include <cuda_bf16.h>
#include <cuda.h>
#include <stdint.h>

typedef __nv_bfloat16 bf16;

constexpr int SEQ = 2048;
constexpr int DM  = 512;
constexpr int NH  = 32;
constexpr int DH  = 128;
constexpr int HD  = NH * DH;
constexpr int FF  = 1376;

__device__ bf16 g_xn[SEQ * DM];
__device__ bf16 g_y [SEQ * DM];
__device__ bf16 g_q [SEQ * HD];
__device__ bf16 g_h [SEQ * FF];
__device__ bf16 g_o [SEQ * HD];

__device__ __forceinline__ uint32_t smem_u32(const void* p) {
    return (uint32_t)__cvta_generic_to_shared(p);
}
__device__ __forceinline__ void mbar_init(uint32_t bar, uint32_t count) {
    asm volatile("mbarrier.init.shared::cta.b64 [%0], %1;" :: "r"(bar), "r"(count) : "memory");
}
__device__ __forceinline__ void mbar_arrive(uint32_t bar) {
    asm volatile("mbarrier.arrive.shared::cta.b64 _, [%0];" :: "r"(bar) : "memory");
}
__device__ __forceinline__ void mbar_expect_tx(uint32_t bar, uint32_t bytes) {
    asm volatile("mbarrier.arrive.expect_tx.shared::cta.b64 _, [%0], %1;" :: "r"(bar), "r"(bytes) : "memory");
}
__device__ __forceinline__ void mbar_wait(uint32_t bar, uint32_t parity) {
    asm volatile(
        "{\n"
        ".reg .pred p;\n"
        "LAB_WAIT:\n"
        "mbarrier.try_wait.parity.shared::cta.b64 p, [%0], %1;\n"
        "@p bra DONE;\n"
        "bra LAB_WAIT;\n"
        "DONE:\n"
        "}\n" :: "r"(bar), "r"(parity) : "memory");
}
__device__ __forceinline__ void tma_load_2d(uint32_t dst, const CUtensorMap* map, uint32_t bar, int c0, int c1) {
    asm volatile(
        "cp.async.bulk.tensor.2d.shared::cluster.global.mbarrier::complete_tx::bytes [%0], [%1, {%3, %4}], [%2];"
        :: "r"(dst), "l"((uint64_t)map), "r"(bar), "r"(c0), "r"(c1) : "memory");
}
__device__ __forceinline__ void wgmma_fence() { asm volatile("wgmma.fence.sync.aligned;" ::: "memory"); }
__device__ __forceinline__ void wgmma_commit() { asm volatile("wgmma.commit_group.sync.aligned;" ::: "memory"); }
template <int N> __device__ __forceinline__ void wgmma_wait() {
    asm volatile("wgmma.wait_group.sync.aligned %0;" :: "n"(N) : "memory");
}
template <int R> __device__ __forceinline__ void reg_alloc() {
    asm volatile("setmaxnreg.inc.sync.aligned.u32 %0;" :: "n"(R));
}
template <int R> __device__ __forceinline__ void reg_dealloc() {
    asm volatile("setmaxnreg.dec.sync.aligned.u32 %0;" :: "n"(R));
}
__device__ __forceinline__ void fence_barrier_init() {
    asm volatile("fence.mbarrier_init.release.cluster;" ::: "memory");
}
__device__ __forceinline__ void fence_proxy_async() {
    asm volatile("fence.proxy.async.shared::cta;" ::: "memory");
}

__device__ __forceinline__ void named_sync(int id, int n) {
    asm volatile("bar.sync %0, %1;" :: "r"(id), "r"(n) : "memory");
}
__device__ __forceinline__ void named_arrive(int id, int n) {
    asm volatile("bar.arrive %0, %1;" :: "r"(id), "r"(n) : "memory");
}
__device__ __forceinline__ float fast_exp2(float x) {
    float y;
    asm("ex2.approx.ftz.f32 %0, %1;" : "=f"(y) : "f"(x));
    return y;
}

__device__ __forceinline__ void st_shared_u32(uint32_t a, uint32_t v) {
    asm volatile("st.shared.u32 [%0], %1;" :: "r"(a), "r"(v) : "memory");
}
__device__ __forceinline__ uint4 ld_shared_v4(uint32_t a) {
    uint4 v;
    asm volatile("ld.shared.v4.u32 {%0,%1,%2,%3}, [%4];" : "=r"(v.x), "=r"(v.y), "=r"(v.z), "=r"(v.w) : "r"(a) : "memory");
    return v;
}

__device__ __forceinline__ uint64_t make_desc(uint32_t addr, uint32_t lbo_bytes, uint32_t sbo_bytes) {
    uint64_t d = 0;
    d |= (uint64_t)((addr & 0x3FFFF) >> 4);
    d |= (uint64_t)((lbo_bytes & 0x3FFFF) >> 4) << 16;
    d |= (uint64_t)((sbo_bytes & 0x3FFFF) >> 4) << 32;
    d |= (uint64_t)1 << 62;
    return d;
}

template <int TA, int TB>
__device__ __forceinline__ void wgmma_m64n128k16_ss(float (&d)[64], uint64_t da, uint64_t db, int scale_d) {
    asm volatile(
        "{\n.reg .pred p;\nsetp.ne.b32 p, %66, 0;\n"
        "wgmma.mma_async.sync.aligned.m64n128k16.f32.bf16.bf16 "
        "{%0,%1,%2,%3,%4,%5,%6,%7,%8,%9,%10,%11,%12,%13,%14,%15,"
        "%16,%17,%18,%19,%20,%21,%22,%23,%24,%25,%26,%27,%28,%29,%30,%31,"
        "%32,%33,%34,%35,%36,%37,%38,%39,%40,%41,%42,%43,%44,%45,%46,%47,"
        "%48,%49,%50,%51,%52,%53,%54,%55,%56,%57,%58,%59,%60,%61,%62,%63},"
        " %64, %65, p, 1, 1, %67, %68;\n}\n"
        : "+f"(d[0]), "+f"(d[1]), "+f"(d[2]), "+f"(d[3]), "+f"(d[4]), "+f"(d[5]), "+f"(d[6]), "+f"(d[7]),
          "+f"(d[8]), "+f"(d[9]), "+f"(d[10]), "+f"(d[11]), "+f"(d[12]), "+f"(d[13]), "+f"(d[14]), "+f"(d[15]),
          "+f"(d[16]), "+f"(d[17]), "+f"(d[18]), "+f"(d[19]), "+f"(d[20]), "+f"(d[21]), "+f"(d[22]), "+f"(d[23]),
          "+f"(d[24]), "+f"(d[25]), "+f"(d[26]), "+f"(d[27]), "+f"(d[28]), "+f"(d[29]), "+f"(d[30]), "+f"(d[31]),
          "+f"(d[32]), "+f"(d[33]), "+f"(d[34]), "+f"(d[35]), "+f"(d[36]), "+f"(d[37]), "+f"(d[38]), "+f"(d[39]),
          "+f"(d[40]), "+f"(d[41]), "+f"(d[42]), "+f"(d[43]), "+f"(d[44]), "+f"(d[45]), "+f"(d[46]), "+f"(d[47]),
          "+f"(d[48]), "+f"(d[49]), "+f"(d[50]), "+f"(d[51]), "+f"(d[52]), "+f"(d[53]), "+f"(d[54]), "+f"(d[55]),
          "+f"(d[56]), "+f"(d[57]), "+f"(d[58]), "+f"(d[59]), "+f"(d[60]), "+f"(d[61]), "+f"(d[62]), "+f"(d[63])
        : "l"(da), "l"(db), "r"(scale_d), "n"(TA), "n"(TB));
}

template <int TB>
__device__ __forceinline__ void wgmma_m64n128k16_rs(float (&d)[64], uint32_t a0, uint32_t a1, uint32_t a2, uint32_t a3,
                                                    uint64_t db, int scale_d) {
    asm volatile(
        "{\n.reg .pred p;\nsetp.ne.b32 p, %69, 0;\n"
        "wgmma.mma_async.sync.aligned.m64n128k16.f32.bf16.bf16 "
        "{%0,%1,%2,%3,%4,%5,%6,%7,%8,%9,%10,%11,%12,%13,%14,%15,"
        "%16,%17,%18,%19,%20,%21,%22,%23,%24,%25,%26,%27,%28,%29,%30,%31,"
        "%32,%33,%34,%35,%36,%37,%38,%39,%40,%41,%42,%43,%44,%45,%46,%47,"
        "%48,%49,%50,%51,%52,%53,%54,%55,%56,%57,%58,%59,%60,%61,%62,%63},"
        " {%64,%65,%66,%67}, %68, p, 1, 1, %70;\n}\n"
        : "+f"(d[0]), "+f"(d[1]), "+f"(d[2]), "+f"(d[3]), "+f"(d[4]), "+f"(d[5]), "+f"(d[6]), "+f"(d[7]),
          "+f"(d[8]), "+f"(d[9]), "+f"(d[10]), "+f"(d[11]), "+f"(d[12]), "+f"(d[13]), "+f"(d[14]), "+f"(d[15]),
          "+f"(d[16]), "+f"(d[17]), "+f"(d[18]), "+f"(d[19]), "+f"(d[20]), "+f"(d[21]), "+f"(d[22]), "+f"(d[23]),
          "+f"(d[24]), "+f"(d[25]), "+f"(d[26]), "+f"(d[27]), "+f"(d[28]), "+f"(d[29]), "+f"(d[30]), "+f"(d[31]),
          "+f"(d[32]), "+f"(d[33]), "+f"(d[34]), "+f"(d[35]), "+f"(d[36]), "+f"(d[37]), "+f"(d[38]), "+f"(d[39]),
          "+f"(d[40]), "+f"(d[41]), "+f"(d[42]), "+f"(d[43]), "+f"(d[44]), "+f"(d[45]), "+f"(d[46]), "+f"(d[47]),
          "+f"(d[48]), "+f"(d[49]), "+f"(d[50]), "+f"(d[51]), "+f"(d[52]), "+f"(d[53]), "+f"(d[54]), "+f"(d[55]),
          "+f"(d[56]), "+f"(d[57]), "+f"(d[58]), "+f"(d[59]), "+f"(d[60]), "+f"(d[61]), "+f"(d[62]), "+f"(d[63])
        : "r"(a0), "r"(a1), "r"(a2), "r"(a3), "l"(db), "r"(scale_d), "n"(TB));
}

__device__ __forceinline__ uint32_t pack_bf16(float lo, float hi) {
    __nv_bfloat162 v = __floats2bfloat162_rn(lo, hi);
    return *reinterpret_cast<uint32_t*>(&v);
}

__global__ void __launch_bounds__(256) ln_kernel(const bf16* __restrict__ x) {
    int warp = threadIdx.x >> 5, lane = threadIdx.x & 31;
    int row = blockIdx.x * 8 + warp;
    const uint4* src = reinterpret_cast<const uint4*>(x + (size_t)row * DM);
    float v[16];
#pragma unroll
    for (int i = 0; i < 2; i++) {
        uint4 u = src[lane + i * 32];
        const __nv_bfloat162* h = reinterpret_cast<const __nv_bfloat162*>(&u);
#pragma unroll
        for (int j = 0; j < 4; j++) {
            float2 f = __bfloat1622float2(h[j]);
            v[i * 8 + j * 2] = f.x; v[i * 8 + j * 2 + 1] = f.y;
        }
    }
#pragma unroll
    for (int pass = 0; pass < 2; pass++) {
        float s = 0.f;
#pragma unroll
        for (int i = 0; i < 16; i++) s += v[i];
#pragma unroll
        for (int o = 16; o > 0; o >>= 1) s += __shfl_xor_sync(0xffffffffu, s, o);
        float mean = s * (1.f / DM);
        float q = 0.f;
#pragma unroll
        for (int i = 0; i < 16; i++) { float d = v[i] - mean; q += d * d; }
#pragma unroll
        for (int o = 16; o > 0; o >>= 1) q += __shfl_xor_sync(0xffffffffu, q, o);
        float rstd = 1.0f / sqrtf(q * (1.f / DM) + 1e-5f);
        bf16* dst = (pass == 0 ? g_xn : g_y) + (size_t)row * DM;
#pragma unroll
        for (int i = 0; i < 2; i++) {
            uint4 u;
            uint32_t* w = reinterpret_cast<uint32_t*>(&u);
#pragma unroll
            for (int j = 0; j < 4; j++) {
                __nv_bfloat162 h = __floats2bfloat162_rn((v[i * 8 + j * 2] - mean) * rstd, (v[i * 8 + j * 2 + 1] - mean) * rstd);
                w[j] = *reinterpret_cast<uint32_t*>(&h);
                float2 f = __bfloat1622float2(h);
                v[i * 8 + j * 2] = f.x; v[i * 8 + j * 2 + 1] = f.y;
            }
            reinterpret_cast<uint4*>(dst)[lane + i * 32] = u;
        }
    }
}

constexpr int G_STAGES = 4;
constexpr int G_STAGE_BYTES = 32768;
constexpr int G_SMEM = G_STAGES * G_STAGE_BYTES + 1024 + 256;

__device__ __forceinline__ float gelu_tanh(float x) {
    float u = 0.7978845608028654f * (x + 0.044715f * x * x * x);
    float t = 1.f - 2.f / (1.f + __expf(2.f * u));
    return 0.5f * x * (1.f + t);
}

template <int MODE>
__global__ void __launch_bounds__(384, 1)
gemm_kernel(const __grid_constant__ CUtensorMap mapA, const __grid_constant__ CUtensorMap mapB,
            bf16* __restrict__ C, int ldc, int N, int K, const bf16* __restrict__ bias) {
    extern __shared__ uint8_t smem_raw[];
    uint32_t sbase = (smem_u32(smem_raw) + 1023) & ~1023u;
    uint32_t bar_full = sbase + G_STAGES * G_STAGE_BYTES;
    uint32_t bar_empty = bar_full + 8 * G_STAGES;
    int wg = threadIdx.x >> 7;
    int tid = threadIdx.x & 127;
    int m0 = blockIdx.y * 128, n0 = blockIdx.x * 128;
    int nk = K / 64;

    if (threadIdx.x == 0) {
        for (int i = 0; i < G_STAGES; i++) { mbar_init(bar_full + 8 * i, 1); mbar_init(bar_empty + 8 * i, 8); }
        fence_barrier_init();
    }
    __syncthreads();

    if (wg == 0) {
        reg_dealloc<40>();
        if (tid == 0) {
            for (int it = 0; it < nk; it++) {
                int s = it % G_STAGES;
                uint32_t ph = (it / G_STAGES) & 1;
                mbar_wait(bar_empty + 8 * s, ph ^ 1);
                mbar_expect_tx(bar_full + 8 * s, G_STAGE_BYTES);
                uint32_t a = sbase + s * G_STAGE_BYTES;
                tma_load_2d(a, &mapA, bar_full + 8 * s, it * 64, m0);
                tma_load_2d(a + 16384, &mapB, bar_full + 8 * s, n0, it * 64);
                tma_load_2d(a + 16384 + 8192, &mapB, bar_full + 8 * s, n0 + 64, it * 64);
            }
        }
    } else {
        reg_alloc<232>();
        float acc[64];
#pragma unroll
        for (int i = 0; i < 64; i++) acc[i] = 0.f;
        int cw = wg - 1;
        for (int it = 0; it < nk; it++) {
            int s = it % G_STAGES;
            uint32_t ph = (it / G_STAGES) & 1;
            mbar_wait(bar_full + 8 * s, ph);
            uint32_t a = sbase + s * G_STAGE_BYTES + cw * 8192;
            uint32_t b = sbase + s * G_STAGE_BYTES + 16384;
            wgmma_fence();
#pragma unroll
            for (int kk = 0; kk < 4; kk++) {
                wgmma_m64n128k16_ss<0, 1>(acc, make_desc(a + kk * 32, 16, 1024), make_desc(b + kk * 2048, 8192, 1024), 1);
            }
            wgmma_commit();
            wgmma_wait<0>();
            if ((tid & 31) == 0) mbar_arrive(bar_empty + 8 * s);
        }
        int warp = tid >> 5, lane = tid & 31;
        int r0 = m0 + cw * 64 + warp * 16 + (lane >> 2);
#pragma unroll
        for (int j = 0; j < 16; j++) {
            int c = n0 + j * 8 + (lane & 3) * 2;
            if (c < N) {
                float v0 = acc[j * 4 + 0], v1 = acc[j * 4 + 1], v2 = acc[j * 4 + 2], v3 = acc[j * 4 + 3];
                if (MODE == 1) {
                    float b0 = __bfloat162float(bias[c]), b1 = __bfloat162float(bias[c + 1]);
                    v0 = gelu_tanh(v0 + b0); v1 = gelu_tanh(v1 + b1);
                    v2 = gelu_tanh(v2 + b0); v3 = gelu_tanh(v3 + b1);
                }
                *reinterpret_cast<uint32_t*>(C + (size_t)r0 * ldc + c) = pack_bf16(v0, v1);
                *reinterpret_cast<uint32_t*>(C + (size_t)(r0 + 8) * ldc + c) = pack_bf16(v2, v3);
            }
        }
    }
}

constexpr int A_KV_STAGES = 2;
constexpr int A_TILE_BYTES = 128 * 128 * 2;
constexpr int A_SMEM = A_TILE_BYTES * (1 + 2 * A_KV_STAGES) + 1024 + 256;

__global__ void __launch_bounds__(384, 1)
attn_kernel(const __grid_constant__ CUtensorMap mapXn, const __grid_constant__ CUtensorMap mapWq,
            const __grid_constant__ CUtensorMap mapK, const __grid_constant__ CUtensorMap mapV) {
    extern __shared__ uint8_t smem_raw[];
    uint32_t sbase = (smem_u32(smem_raw) + 1023) & ~1023u;
    uint32_t sQ = sbase;
    uint32_t sK = sQ + A_TILE_BYTES;
    uint32_t sV = sK + A_KV_STAGES * A_TILE_BYTES;
    uint32_t bars = sV + A_KV_STAGES * A_TILE_BYTES;
    uint32_t bar_pf = bars, bar_pe = bars + 32;
    uint32_t bar_kf = bars + 64, bar_ke = bar_kf + 8 * A_KV_STAGES;
    uint32_t bar_vf = bar_ke + 8 * A_KV_STAGES, bar_ve = bar_vf + 8 * A_KV_STAGES;
    int wg = threadIdx.x >> 7;
    int tid = threadIdx.x & 127;
    int qt = blockIdx.x, head = blockIdx.y;
    constexpr int NT = SEQ / 128;

    if (threadIdx.x == 0) {
        for (int i = 0; i < 4; i++) { mbar_init(bar_pf + 8 * i, 1); mbar_init(bar_pe + 8 * i, 8); }
        for (int i = 0; i < A_KV_STAGES; i++) {
            mbar_init(bar_kf + 8 * i, 1); mbar_init(bar_ke + 8 * i, 8);
            mbar_init(bar_vf + 8 * i, 1); mbar_init(bar_ve + 8 * i, 8);
        }
        fence_barrier_init();
    }
    __syncthreads();

    if (wg == 0) {
        reg_dealloc<40>();
        if (tid == 0) {
            for (int i = 0; i < 8; i++) {
                int b = i & 3;
                uint32_t buf = sK + b * A_TILE_BYTES;
                mbar_wait(bar_pe + 8 * b, ((i >> 2) & 1) ^ 1);
                mbar_expect_tx(bar_pf + 8 * b, A_TILE_BYTES);
                tma_load_2d(buf, &mapXn, bar_pf + 8 * b, i * 64, qt * 128);
                tma_load_2d(buf + 16384, &mapWq, bar_pf + 8 * b, head * DH, i * 64);
                tma_load_2d(buf + 16384 + 8192, &mapWq, bar_pf + 8 * b, head * DH + 64, i * 64);
            }
            for (int it = 0; it < NT; it++) {
                int s = it % A_KV_STAGES;
                uint32_t ph = (it / A_KV_STAGES) & 1;
                int row = head * SEQ + it * 128;
                if (it < A_KV_STAGES) mbar_wait(bar_pe + 8 * s, 1);
                else mbar_wait(bar_ke + 8 * s, ph ^ 1);
                mbar_expect_tx(bar_kf + 8 * s, A_TILE_BYTES);
                tma_load_2d(sK + s * A_TILE_BYTES, &mapK, bar_kf + 8 * s, 0, row);
                tma_load_2d(sK + s * A_TILE_BYTES + 16384, &mapK, bar_kf + 8 * s, 64, row);
                if (it < A_KV_STAGES) mbar_wait(bar_pe + 8 * (A_KV_STAGES + s), 1);
                else mbar_wait(bar_ve + 8 * s, ph ^ 1);
                mbar_expect_tx(bar_vf + 8 * s, A_TILE_BYTES);
                tma_load_2d(sV + s * A_TILE_BYTES, &mapV, bar_vf + 8 * s, 0, row);
                tma_load_2d(sV + s * A_TILE_BYTES + 16384, &mapV, bar_vf + 8 * s, 64, row);
            }
        }
    } else {
        reg_alloc<232>();
        int cw = wg - 1;
        int warp = tid >> 5, lane = tid & 31;
        float o[64];
        for (int i = 0; i < 8; i++) {
            int b = i & 3;
            uint32_t buf = sK + b * A_TILE_BYTES;
            mbar_wait(bar_pf + 8 * b, (i >> 2) & 1);
            wgmma_fence();
#pragma unroll
            for (int kk = 0; kk < 4; kk++)
                wgmma_m64n128k16_ss<0, 1>(o, make_desc(buf + cw * 8192 + kk * 32, 16, 1024),
                                          make_desc(buf + 16384 + kk * 2048, 8192, 1024), (i | kk) != 0);
            wgmma_commit();
            wgmma_wait<0>();
            if (lane == 0) mbar_arrive(bar_pe + 8 * b);
        }
        {
            int r = cw * 64 + warp * 16 + (lane >> 2);
#pragma unroll
            for (int j = 0; j < 16; j++) {
                uint32_t a = sQ + (j >> 3) * 16384 + r * 128 + (((j & 7) ^ (r & 7)) << 4) + (lane & 3) * 4;
                st_shared_u32(a, pack_bf16(o[j * 4 + 0], o[j * 4 + 1]));
                st_shared_u32(a + 1024, pack_bf16(o[j * 4 + 2], o[j * 4 + 3]));
            }
            fence_proxy_async();
            named_sync(3 + cw, 128);
        }
#pragma unroll
        for (int i = 0; i < 64; i++) o[i] = 0.f;
        float m0 = -INFINITY, m1 = -INFINITY, l0 = 0.f, l1 = 0.f;
        const float sc = 0.08838834764831845f * 1.4426950408889634f;
        if (cw == 1) named_arrive(1, 256);
        uint32_t qa = sQ + cw * 8192;
        float sacc[64];
        uint32_t p[32];
        mbar_wait(bar_kf, 0);
        named_sync(1 + cw, 256);
        wgmma_fence();
#pragma unroll
        for (int kk = 0; kk < 8; kk++) {
            uint32_t off = (kk >> 2) * 16384 + (kk & 3) * 32;
            wgmma_m64n128k16_ss<0, 0>(sacc, make_desc(qa + off, 16, 1024), make_desc(sK + off, 16, 1024), kk != 0);
        }
        wgmma_commit();
        named_arrive(1 + (cw ^ 1), 256);
        wgmma_wait<0>();
        if (lane == 0) mbar_arrive(bar_ke);
        {
            float mx0 = -INFINITY, mx1 = -INFINITY;
#pragma unroll
            for (int j = 0; j < 16; j++) {
                mx0 = fmaxf(mx0, fmaxf(sacc[j * 4 + 0], sacc[j * 4 + 1]));
                mx1 = fmaxf(mx1, fmaxf(sacc[j * 4 + 2], sacc[j * 4 + 3]));
            }
            mx0 = fmaxf(mx0, __shfl_xor_sync(0xffffffffu, mx0, 1));
            mx0 = fmaxf(mx0, __shfl_xor_sync(0xffffffffu, mx0, 2));
            mx1 = fmaxf(mx1, __shfl_xor_sync(0xffffffffu, mx1, 1));
            mx1 = fmaxf(mx1, __shfl_xor_sync(0xffffffffu, mx1, 2));
            m0 = mx0; m1 = mx1;
            float ms0 = mx0 * sc, ms1 = mx1 * sc;
#pragma unroll
            for (int j = 0; j < 16; j++) {
                float p0 = fast_exp2(sacc[j * 4 + 0] * sc - ms0);
                float p1 = fast_exp2(sacc[j * 4 + 1] * sc - ms0);
                float p2 = fast_exp2(sacc[j * 4 + 2] * sc - ms1);
                float p3 = fast_exp2(sacc[j * 4 + 3] * sc - ms1);
                l0 += p0 + p1; l1 += p2 + p3;
                p[j * 2 + 0] = pack_bf16(p0, p1);
                p[j * 2 + 1] = pack_bf16(p2, p3);
            }
        }
        for (int it = 1; it < NT; it++) {
            int s = it % A_KV_STAGES;
            uint32_t ph = (it / A_KV_STAGES) & 1;
            int sp = (it - 1) % A_KV_STAGES;
            uint32_t php = ((it - 1) / A_KV_STAGES) & 1;
            mbar_wait(bar_kf + 8 * s, ph);
            named_sync(1 + cw, 256);
            uint32_t kb = sK + s * A_TILE_BYTES;
            wgmma_fence();
#pragma unroll
            for (int kk = 0; kk < 8; kk++) {
                uint32_t off = (kk >> 2) * 16384 + (kk & 3) * 32;
                wgmma_m64n128k16_ss<0, 0>(sacc, make_desc(qa + off, 16, 1024), make_desc(kb + off, 16, 1024), kk != 0);
            }
            wgmma_commit();
            mbar_wait(bar_vf + 8 * sp, php);
            uint32_t vb = sV + sp * A_TILE_BYTES;
#pragma unroll
            for (int kk = 0; kk < 8; kk++) {
                wgmma_m64n128k16_rs<1>(o, p[kk * 4 + 0], p[kk * 4 + 1], p[kk * 4 + 2], p[kk * 4 + 3],
                                       make_desc(vb + kk * 2048, 16384, 1024), 1);
            }
            wgmma_commit();
            named_arrive(1 + (cw ^ 1), 256);
            wgmma_wait<1>();
            if (lane == 0) mbar_arrive(bar_ke + 8 * s);
            float mx0 = m0, mx1 = m1;
#pragma unroll
            for (int j = 0; j < 16; j++) {
                mx0 = fmaxf(mx0, fmaxf(sacc[j * 4 + 0], sacc[j * 4 + 1]));
                mx1 = fmaxf(mx1, fmaxf(sacc[j * 4 + 2], sacc[j * 4 + 3]));
            }
            mx0 = fmaxf(mx0, __shfl_xor_sync(0xffffffffu, mx0, 1));
            mx0 = fmaxf(mx0, __shfl_xor_sync(0xffffffffu, mx0, 2));
            mx1 = fmaxf(mx1, __shfl_xor_sync(0xffffffffu, mx1, 1));
            mx1 = fmaxf(mx1, __shfl_xor_sync(0xffffffffu, mx1, 2));
            float c0 = fast_exp2((m0 - mx0) * sc), c1 = fast_exp2((m1 - mx1) * sc);
            m0 = mx0; m1 = mx1;
            float ms0 = mx0 * sc, ms1 = mx1 * sc;
            float rs0 = 0.f, rs1 = 0.f;
#pragma unroll
            for (int j = 0; j < 16; j++) {
                sacc[j * 4 + 0] = fast_exp2(sacc[j * 4 + 0] * sc - ms0);
                sacc[j * 4 + 1] = fast_exp2(sacc[j * 4 + 1] * sc - ms0);
                sacc[j * 4 + 2] = fast_exp2(sacc[j * 4 + 2] * sc - ms1);
                sacc[j * 4 + 3] = fast_exp2(sacc[j * 4 + 3] * sc - ms1);
                rs0 += sacc[j * 4 + 0] + sacc[j * 4 + 1]; rs1 += sacc[j * 4 + 2] + sacc[j * 4 + 3];
            }
            l0 = l0 * c0 + rs0; l1 = l1 * c1 + rs1;
            wgmma_wait<0>();
            if (lane == 0) mbar_arrive(bar_ve + 8 * sp);
#pragma unroll
            for (int j = 0; j < 16; j++) {
                o[j * 4 + 0] *= c0; o[j * 4 + 1] *= c0; o[j * 4 + 2] *= c1; o[j * 4 + 3] *= c1;
                p[j * 2 + 0] = pack_bf16(sacc[j * 4 + 0], sacc[j * 4 + 1]);
                p[j * 2 + 1] = pack_bf16(sacc[j * 4 + 2], sacc[j * 4 + 3]);
            }
        }
        {
            int sp = (NT - 1) % A_KV_STAGES;
            uint32_t php = ((NT - 1) / A_KV_STAGES) & 1;
            mbar_wait(bar_vf + 8 * sp, php);
            uint32_t vb = sV + sp * A_TILE_BYTES;
            wgmma_fence();
#pragma unroll
            for (int kk = 0; kk < 8; kk++) {
                wgmma_m64n128k16_rs<1>(o, p[kk * 4 + 0], p[kk * 4 + 1], p[kk * 4 + 2], p[kk * 4 + 3],
                                       make_desc(vb + kk * 2048, 16384, 1024), 1);
            }
            wgmma_commit();
            wgmma_wait<0>();
        }
        l0 += __shfl_xor_sync(0xffffffffu, l0, 1);
        l0 += __shfl_xor_sync(0xffffffffu, l0, 2);
        l1 += __shfl_xor_sync(0xffffffffu, l1, 1);
        l1 += __shfl_xor_sync(0xffffffffu, l1, 2);
        float i0 = 1.f / l0, i1 = 1.f / l1;
        {
            int r = cw * 64 + warp * 16 + (lane >> 2);
#pragma unroll
            for (int j = 0; j < 16; j++) {
                uint32_t a = sQ + (j >> 3) * 16384 + r * 128 + (((j & 7) ^ (r & 7)) << 4) + (lane & 3) * 4;
                st_shared_u32(a, pack_bf16(o[j * 4 + 0] * i0, o[j * 4 + 1] * i0));
                st_shared_u32(a + 1024, pack_bf16(o[j * 4 + 2] * i1, o[j * 4 + 3] * i1));
            }
            named_sync(3 + cw, 128);
#pragma unroll
            for (int i = 0; i < 8; i++) {
                int idx = i * 128 + tid;
                int rr = cw * 64 + (idx >> 4), ch = idx & 15;
                uint32_t a = sQ + (ch >> 3) * 16384 + rr * 128 + (((ch & 7) ^ (rr & 7)) << 4);
                uint4 v = ld_shared_v4(a);
                *reinterpret_cast<uint4*>(g_o + (size_t)(qt * 128 + rr) * HD + head * DH + ch * 8) = v;
            }
        }
    }
}

__global__ void __launch_bounds__(384, 1)
final_kernel(const __grid_constant__ CUtensorMap mapO, const __grid_constant__ CUtensorMap mapWo,
             const __grid_constant__ CUtensorMap mapH, const __grid_constant__ CUtensorMap mapW2,
             const bf16* __restrict__ x, const bf16* __restrict__ b2, bf16* __restrict__ out) {
    extern __shared__ uint8_t smem_raw[];
    uint32_t sbase = (smem_u32(smem_raw) + 1023) & ~1023u;
    uint32_t bar_full = sbase + G_STAGES * G_STAGE_BYTES;
    uint32_t bar_empty = bar_full + 8 * G_STAGES;
    int wg = threadIdx.x >> 7;
    int tid = threadIdx.x & 127;
    int m0 = blockIdx.y * 128, n0 = blockIdx.x * 128;
    constexpr int NK1 = HD / 64;
    constexpr int NK2 = (FF + 63) / 64;

    if (threadIdx.x == 0) {
        for (int i = 0; i < G_STAGES; i++) { mbar_init(bar_full + 8 * i, 1); mbar_init(bar_empty + 8 * i, 8); }
        fence_barrier_init();
    }
    __syncthreads();

    if (wg == 0) {
        reg_dealloc<40>();
        if (tid == 0) {
            for (int it = 0; it < NK1 + NK2; it++) {
                int s = it % G_STAGES;
                uint32_t ph = (it / G_STAGES) & 1;
                mbar_wait(bar_empty + 8 * s, ph ^ 1);
                mbar_expect_tx(bar_full + 8 * s, G_STAGE_BYTES);
                uint32_t a = sbase + s * G_STAGE_BYTES;
                const CUtensorMap* pa = it < NK1 ? &mapO : &mapH;
                const CUtensorMap* pb = it < NK1 ? &mapWo : &mapW2;
                int k = (it < NK1 ? it : it - NK1) * 64;
                tma_load_2d(a, pa, bar_full + 8 * s, k, m0);
                tma_load_2d(a + 16384, pb, bar_full + 8 * s, n0, k);
                tma_load_2d(a + 16384 + 8192, pb, bar_full + 8 * s, n0 + 64, k);
            }
        }
    } else {
        reg_alloc<232>();
        float acc[64], acc2[64];
#pragma unroll
        for (int i = 0; i < 64; i++) { acc[i] = 0.f; acc2[i] = 0.f; }
        int cw = wg - 1;
        for (int it = 0; it < NK1; it++) {
            int s = it % G_STAGES;
            uint32_t ph = (it / G_STAGES) & 1;
            mbar_wait(bar_full + 8 * s, ph);
            uint32_t a = sbase + s * G_STAGE_BYTES + cw * 8192;
            uint32_t b = sbase + s * G_STAGE_BYTES + 16384;
            wgmma_fence();
#pragma unroll
            for (int kk = 0; kk < 4; kk++)
                wgmma_m64n128k16_ss<0, 1>(acc, make_desc(a + kk * 32, 16, 1024), make_desc(b + kk * 2048, 8192, 1024), 1);
            wgmma_commit();
            wgmma_wait<0>();
            if ((tid & 31) == 0) mbar_arrive(bar_empty + 8 * s);
        }
        for (int it = NK1; it < NK1 + NK2; it++) {
            int s = it % G_STAGES;
            uint32_t ph = (it / G_STAGES) & 1;
            mbar_wait(bar_full + 8 * s, ph);
            uint32_t a = sbase + s * G_STAGE_BYTES + cw * 8192;
            uint32_t b = sbase + s * G_STAGE_BYTES + 16384;
            wgmma_fence();
#pragma unroll
            for (int kk = 0; kk < 4; kk++)
                wgmma_m64n128k16_ss<0, 1>(acc2, make_desc(a + kk * 32, 16, 1024), make_desc(b + kk * 2048, 8192, 1024), 1);
            wgmma_commit();
            wgmma_wait<0>();
            if ((tid & 31) == 0) mbar_arrive(bar_empty + 8 * s);
        }
        int warp = tid >> 5, lane = tid & 31;
        int r0 = m0 + cw * 64 + warp * 16 + (lane >> 2);
#pragma unroll
        for (int j = 0; j < 16; j++) {
            int c = n0 + j * 8 + (lane & 3) * 2;
            float b0 = __bfloat162float(b2[c]), b1 = __bfloat162float(b2[c + 1]);
#pragma unroll
            for (int h = 0; h < 2; h++) {
                int r = r0 + h * 8;
                float2 xv = __bfloat1622float2(*reinterpret_cast<const __nv_bfloat162*>(x + (size_t)r * DM + c));
                float g0 = acc2[j * 4 + h * 2 + 0] + b0, g1 = acc2[j * 4 + h * 2 + 1] + b1;
                g0 = g0 / (1.f + __expf(-g0)); g1 = g1 / (1.f + __expf(-g1));
                float o0 = xv.x + acc[j * 4 + h * 2 + 0] * g0;
                float o1 = xv.y + acc[j * 4 + h * 2 + 1] * g1;
                *reinterpret_cast<uint32_t*>(out + (size_t)r * DM + c) = pack_bf16(o0, o1);
            }
        }
    }
}

typedef CUresult (*EncodeFn)(CUtensorMap*, CUtensorMapDataType, cuuint32_t, void*, const cuuint64_t*, const cuuint64_t*,
                             const cuuint32_t*, const cuuint32_t*, CUtensorMapInterleave, CUtensorMapSwizzle,
                             CUtensorMapL2promotion, CUtensorMapFloatOOBfill);

static void make_map(EncodeFn fn, CUtensorMap* m, const void* ptr, uint64_t inner, uint64_t outer,
                     uint32_t box_inner, uint32_t box_outer) {
    cuuint64_t dims[2] = {inner, outer};
    cuuint64_t strides[1] = {inner * 2};
    cuuint32_t box[2] = {box_inner, box_outer};
    cuuint32_t es[2] = {1, 1};
    fn(m, CU_TENSOR_MAP_DATA_TYPE_BFLOAT16, 2, const_cast<void*>(ptr), dims, strides, box, es,
       CU_TENSOR_MAP_INTERLEAVE_NONE, CU_TENSOR_MAP_SWIZZLE_128B, CU_TENSOR_MAP_L2_PROMOTION_L2_256B,
       CU_TENSOR_MAP_FLOAT_OOB_FILL_NONE);
}

extern "C" void kernel_launch(void* const* d_in, const int* in_sizes, int n_in, void* d_out, int out_size) {
    const bf16* x  = (const bf16*)d_in[0];
    const bf16* kc = (const bf16*)d_in[1];
    const bf16* vc = (const bf16*)d_in[2];
    const bf16* wq = (const bf16*)d_in[3];
    const bf16* wo = (const bf16*)d_in[4];
    const bf16* w1 = (const bf16*)d_in[6];
    const bf16* b1 = (const bf16*)d_in[7];
    const bf16* w2 = (const bf16*)d_in[8];
    const bf16* b2 = (const bf16*)d_in[9];
    bf16* out = (bf16*)d_out;

    static bool inited = false;
    static CUtensorMap mXn, mY, mWq, mW1, mQ, mK, mV, mO, mWo, mH, mW2;
    static void *pq, *ph;
    if (!inited) {
        EncodeFn fn = nullptr;
        cudaDriverEntryPointQueryResult qres;
        cudaGetDriverEntryPoint("cuTensorMapEncodeTiled", (void**)&fn, cudaEnableDefault, &qres);
        void *pxn, *py, *po;
        cudaGetSymbolAddress(&pxn, g_xn); cudaGetSymbolAddress(&py, g_y); cudaGetSymbolAddress(&pq, g_q);
        cudaGetSymbolAddress(&ph, g_h); cudaGetSymbolAddress(&po, g_o);
        make_map(fn, &mXn, pxn, DM, SEQ, 64, 128);
        make_map(fn, &mY, py, DM, SEQ, 64, 128);
        make_map(fn, &mWq, wq, HD, DM, 64, 64);
        make_map(fn, &mW1, w1, FF, DM, 64, 64);
        make_map(fn, &mQ, pq, HD, SEQ, 64, 128);
        make_map(fn, &mK, kc, DH, NH * SEQ, 64, 128);
        make_map(fn, &mV, vc, DH, NH * SEQ, 64, 128);
        make_map(fn, &mO, po, HD, SEQ, 64, 128);
        make_map(fn, &mWo, wo, DM, HD, 64, 64);
        make_map(fn, &mH, ph, FF, SEQ, 64, 128);
        make_map(fn, &mW2, w2, DM, FF, 64, 64);
        cudaFuncSetAttribute(gemm_kernel<0>, cudaFuncAttributeMaxDynamicSharedMemorySize, G_SMEM);
        cudaFuncSetAttribute(gemm_kernel<1>, cudaFuncAttributeMaxDynamicSharedMemorySize, G_SMEM);
        cudaFuncSetAttribute(final_kernel, cudaFuncAttributeMaxDynamicSharedMemorySize, G_SMEM);
        cudaFuncSetAttribute(attn_kernel, cudaFuncAttributeMaxDynamicSharedMemorySize, A_SMEM);
        inited = true;
    }

    ln_kernel<<<SEQ / 8, 256>>>(x);
    gemm_kernel<1><<<dim3((FF + 127) / 128, SEQ / 128), 384, G_SMEM>>>(mY, mW1, (bf16*)ph, FF, FF, DM, b1);
    attn_kernel<<<dim3(SEQ / 128, NH), 384, A_SMEM>>>(mXn, mWq, mK, mV);
    final_kernel<<<dim3(DM / 128, SEQ / 128), 384, G_SMEM>>>(mO, mWo, mH, mW2, x, b2, out);
}
```

```cpp
#include <cuda_runtime.h>
#include <cuda_bf16.h>
#include <cuda.h>
#include <stdint.h>

typedef __nv_bfloat16 bf16;

constexpr int SEQ = 2048;
constexpr int DM  = 512;
constexpr int NH  = 32;
constexpr int DH  = 128;
constexpr int HD  = NH * DH;
constexpr int FF  = 1376;

__device__ bf16 g_xn[SEQ * DM];
__device__ bf16 g_y [SEQ * DM];
__device__ bf16 g_q [SEQ * HD];
__device__ bf16 g_h [SEQ * FF];
__device__ bf16 g_o [SEQ * HD];

__device__ __forceinline__ uint32_t smem_u32(const void* p) {
    return (uint32_t)__cvta_generic_to_shared(p);
}
__device__ __forceinline__ void mbar_init(uint32_t bar, uint32_t count) {
    asm volatile("mbarrier.init.shared::cta.b64 [%0], %1;" :: "r"(bar), "r"(count) : "memory");
}
__device__ __forceinline__ void mbar_arrive(uint32_t bar) {
    asm volatile("mbarrier.arrive.shared::cta.b64 _, [%0];" :: "r"(bar) : "memory");
}
__device__ __forceinline__ void mbar_expect_tx(uint32_t bar, uint32_t bytes) {
    asm volatile("mbarrier.arrive.expect_tx.shared::cta.b64 _, [%0], %1;" :: "r"(bar), "r"(bytes) : "memory");
}
__device__ __forceinline__ void mbar_wait(uint32_t bar, uint32_t parity) {
    asm volatile(
        "{\n"
        ".reg .pred p;\n"
        "LAB_WAIT:\n"
        "mbarrier.try_wait.parity.shared::cta.b64 p, [%0], %1;\n"
        "@p bra DONE;\n"
        "bra LAB_WAIT;\n"
        "DONE:\n"
        "}\n" :: "r"(bar), "r"(parity) : "memory");
}
__device__ __forceinline__ void tma_load_2d(uint32_t dst, const CUtensorMap* map, uint32_t bar, int c0, int c1) {
    asm volatile(
        "cp.async.bulk.tensor.2d.shared::cluster.global.mbarrier::complete_tx::bytes [%0], [%1, {%3, %4}], [%2];"
        :: "r"(dst), "l"((uint64_t)map), "r"(bar), "r"(c0), "r"(c1) : "memory");
}
__device__ __forceinline__ void wgmma_fence() { asm volatile("wgmma.fence.sync.aligned;" ::: "memory"); }
__device__ __forceinline__ void wgmma_commit() { asm volatile("wgmma.commit_group.sync.aligned;" ::: "memory"); }
template <int N> __device__ __forceinline__ void wgmma_wait() {
    asm volatile("wgmma.wait_group.sync.aligned %0;" :: "n"(N) : "memory");
}
template <int R> __device__ __forceinline__ void reg_alloc() {
    asm volatile("setmaxnreg.inc.sync.aligned.u32 %0;" :: "n"(R));
}
template <int R> __device__ __forceinline__ void reg_dealloc() {
    asm volatile("setmaxnreg.dec.sync.aligned.u32 %0;" :: "n"(R));
}
__device__ __forceinline__ void fence_barrier_init() {
    asm volatile("fence.mbarrier_init.release.cluster;" ::: "memory");
}
__device__ __forceinline__ void fence_proxy_async() {
    asm volatile("fence.proxy.async.shared::cta;" ::: "memory");
}

__device__ __forceinline__ void named_sync(int id, int n) {
    asm volatile("bar.sync %0, %1;" :: "r"(id), "r"(n) : "memory");
}
__device__ __forceinline__ void named_arrive(int id, int n) {
    asm volatile("bar.arrive %0, %1;" :: "r"(id), "r"(n) : "memory");
}
__device__ __forceinline__ float fast_exp2(float x) {
    float y;
    asm("ex2.approx.ftz.f32 %0, %1;" : "=f"(y) : "f"(x));
    return y;
}

__device__ __forceinline__ void st_shared_u32(uint32_t a, uint32_t v) {
    asm volatile("st.shared.u32 [%0], %1;" :: "r"(a), "r"(v) : "memory");
}
__device__ __forceinline__ uint4 ld_shared_v4(uint32_t a) {
    uint4 v;
    asm volatile("ld.shared.v4.u32 {%0,%1,%2,%3}, [%4];" : "=r"(v.x), "=r"(v.y), "=r"(v.z), "=r"(v.w) : "r"(a) : "memory");
    return v;
}

__device__ __forceinline__ uint64_t make_desc(uint32_t addr, uint32_t lbo_bytes, uint32_t sbo_bytes) {
    uint64_t d = 0;
    d |= (uint64_t)((addr & 0x3FFFF) >> 4);
    d |= (uint64_t)((lbo_bytes & 0x3FFFF) >> 4) << 16;
    d |= (uint64_t)((sbo_bytes & 0x3FFFF) >> 4) << 32;
    d |= (uint64_t)1 << 62;
    return d;
}

template <int TA, int TB>
__device__ __forceinline__ void wgmma_m64n128k16_ss(float (&d)[64], uint64_t da, uint64_t db, int scale_d) {
    asm volatile(
        "{\n.reg .pred p;\nsetp.ne.b32 p, %66, 0;\n"
        "wgmma.mma_async.sync.aligned.m64n128k16.f32.bf16.bf16 "
        "{%0,%1,%2,%3,%4,%5,%6,%7,%8,%9,%10,%11,%12,%13,%14,%15,"
        "%16,%17,%18,%19,%20,%21,%22,%23,%24,%25,%26,%27,%28,%29,%30,%31,"
        "%32,%33,%34,%35,%36,%37,%38,%39,%40,%41,%42,%43,%44,%45,%46,%47,"
        "%48,%49,%50,%51,%52,%53,%54,%55,%56,%57,%58,%59,%60,%61,%62,%63},"
        " %64, %65, p, 1, 1, %67, %68;\n}\n"
        : "+f"(d[0]), "+f"(d[1]), "+f"(d[2]), "+f"(d[3]), "+f"(d[4]), "+f"(d[5]), "+f"(d[6]), "+f"(d[7]),
          "+f"(d[8]), "+f"(d[9]), "+f"(d[10]), "+f"(d[11]), "+f"(d[12]), "+f"(d[13]), "+f"(d[14]), "+f"(d[15]),
          "+f"(d[16]), "+f"(d[17]), "+f"(d[18]), "+f"(d[19]), "+f"(d[20]), "+f"(d[21]), "+f"(d[22]), "+f"(d[23]),
          "+f"(d[24]), "+f"(d[25]), "+f"(d[26]), "+f"(d[27]), "+f"(d[28]), "+f"(d[29]), "+f"(d[30]), "+f"(d[31]),
          "+f"(d[32]), "+f"(d[33]), "+f"(d[34]), "+f"(d[35]), "+f"(d[36]), "+f"(d[37]), "+f"(d[38]), "+f"(d[39]),
          "+f"(d[40]), "+f"(d[41]), "+f"(d[42]), "+f"(d[43]), "+f"(d[44]), "+f"(d[45]), "+f"(d[46]), "+f"(d[47]),
          "+f"(d[48]), "+f"(d[49]), "+f"(d[50]), "+f"(d[51]), "+f"(d[52]), "+f"(d[53]), "+f"(d[54]), "+f"(d[55]),
          "+f"(d[56]), "+f"(d[57]), "+f"(d[58]), "+f"(d[59]), "+f"(d[60]), "+f"(d[61]), "+f"(d[62]), "+f"(d[63])
        : "l"(da), "l"(db), "r"(scale_d), "n"(TA), "n"(TB));
}

template <int TB>
__device__ __forceinline__ void wgmma_m64n128k16_rs(float (&d)[64], uint32_t a0, uint32_t a1, uint32_t a2, uint32_t a3,
                                                    uint64_t db, int scale_d) {
    asm volatile(
        "{\n.reg .pred p;\nsetp.ne.b32 p, %69, 0;\n"
        "wgmma.mma_async.sync.aligned.m64n128k16.f32.bf16.bf16 "
        "{%0,%1,%2,%3,%4,%5,%6,%7,%8,%9,%10,%11,%12,%13,%14,%15,"
        "%16,%17,%18,%19,%20,%21,%22,%23,%24,%25,%26,%27,%28,%29,%30,%31,"
        "%32,%33,%34,%35,%36,%37,%38,%39,%40,%41,%42,%43,%44,%45,%46,%47,"
        "%48,%49,%50,%51,%52,%53,%54,%55,%56,%57,%58,%59,%60,%61,%62,%63},"
        " {%64,%65,%66,%67}, %68, p, 1, 1, %70;\n}\n"
        : "+f"(d[0]), "+f"(d[1]), "+f"(d[2]), "+f"(d[3]), "+f"(d[4]), "+f"(d[5]), "+f"(d[6]), "+f"(d[7]),
          "+f"(d[8]), "+f"(d[9]), "+f"(d[10]), "+f"(d[11]), "+f"(d[12]), "+f"(d[13]), "+f"(d[14]), "+f"(d[15]),
          "+f"(d[16]), "+f"(d[17]), "+f"(d[18]), "+f"(d[19]), "+f"(d[20]), "+f"(d[21]), "+f"(d[22]), "+f"(d[23]),
          "+f"(d[24]), "+f"(d[25]), "+f"(d[26]), "+f"(d[27]), "+f"(d[28]), "+f"(d[29]), "+f"(d[30]), "+f"(d[31]),
          "+f"(d[32]), "+f"(d[33]), "+f"(d[34]), "+f"(d[35]), "+f"(d[36]), "+f"(d[37]), "+f"(d[38]), "+f"(d[39]),
          "+f"(d[40]), "+f"(d[41]), "+f"(d[42]), "+f"(d[43]), "+f"(d[44]), "+f"(d[45]), "+f"(d[46]), "+f"(d[47]),
          "+f"(d[48]), "+f"(d[49]), "+f"(d[50]), "+f"(d[51]), "+f"(d[52]), "+f"(d[53]), "+f"(d[54]), "+f"(d[55]),
          "+f"(d[56]), "+f"(d[57]), "+f"(d[58]), "+f"(d[59]), "+f"(d[60]), "+f"(d[61]), "+f"(d[62]), "+f"(d[63])
        : "r"(a0), "r"(a1), "r"(a2), "r"(a3), "l"(db), "r"(scale_d), "n"(TB));
}

__device__ __forceinline__ uint32_t pack_bf16(float lo, float hi) {
    __nv_bfloat162 v = __floats2bfloat162_rn(lo, hi);
    return *reinterpret_cast<uint32_t*>(&v);
}

__global__ void __launch_bounds__(256) ln_kernel(const bf16* __restrict__ x) {
    int warp = threadIdx.x >> 5, lane = threadIdx.x & 31;
    int row = blockIdx.x * 8 + warp;
    const uint4* src = reinterpret_cast<const uint4*>(x + (size_t)row * DM);
    float v[16];
#pragma unroll
    for (int i = 0; i < 2; i++) {
        uint4 u = src[lane + i * 32];
        const __nv_bfloat162* h = reinterpret_cast<const __nv_bfloat162*>(&u);
#pragma unroll
        for (int j = 0; j < 4; j++) {
            float2 f = __bfloat1622float2(h[j]);
            v[i * 8 + j * 2] = f.x; v[i * 8 + j * 2 + 1] = f.y;
        }
    }
#pragma unroll
    for (int pass = 0; pass < 2; pass++) {
        float s = 0.f;
#pragma unroll
        for (int i = 0; i < 16; i++) s += v[i];
#pragma unroll
        for (int o = 16; o > 0; o >>= 1) s += __shfl_xor_sync(0xffffffffu, s, o);
        float mean = s * (1.f / DM);
        float q = 0.f;
#pragma unroll
        for (int i = 0; i < 16; i++) { float d = v[i] - mean; q += d * d; }
#pragma unroll
        for (int o = 16; o > 0; o >>= 1) q += __shfl_xor_sync(0xffffffffu, q, o);
        float rstd = 1.0f / sqrtf(q * (1.f / DM) + 1e-5f);
        bf16* dst = (pass == 0 ? g_xn : g_y) + (size_t)row * DM;
#pragma unroll
        for (int i = 0; i < 2; i++) {
            uint4 u;
            uint32_t* w = reinterpret_cast<uint32_t*>(&u);
#pragma unroll
            for (int j = 0; j < 4; j++) {
                __nv_bfloat162 h = __floats2bfloat162_rn((v[i * 8 + j * 2] - mean) * rstd, (v[i * 8 + j * 2 + 1] - mean) * rstd);
                w[j] = *reinterpret_cast<uint32_t*>(&h);
                float2 f = __bfloat1622float2(h);
                v[i * 8 + j * 2] = f.x; v[i * 8 + j * 2 + 1] = f.y;
            }
            reinterpret_cast<uint4*>(dst)[lane + i * 32] = u;
        }
    }
}

constexpr int G_STAGE_BYTES = 8192 + 16384;

__device__ __forceinline__ float gelu_tanh(float x) {
    float u = 0.7978845608028654f * (x + 0.044715f * x * x * x);
    float t = 1.f - 2.f / (1.f + __expf(2.f * u));
    return 0.5f * x * (1.f + t);
}

constexpr int M1_STAGES = 4;
constexpr int M1_SMEM = M1_STAGES * G_STAGE_BYTES + 1024 + 256;
__global__ void __launch_bounds__(256, 2)
mlp1_kernel(const __grid_constant__ CUtensorMap mapA, const __grid_constant__ CUtensorMap mapB,
            bf16* __restrict__ C, const bf16* __restrict__ bias) {
    extern __shared__ uint8_t smem_raw[];
    uint32_t sbase = (smem_u32(smem_raw) + 1023) & ~1023u;
    uint32_t bar_full = sbase + M1_STAGES * G_STAGE_BYTES;
    uint32_t bar_empty = bar_full + 8 * M1_STAGES;
    int wg = threadIdx.x >> 7;
    int tid = threadIdx.x & 127;
    int m0 = blockIdx.y * 64, n0 = blockIdx.x * 128;
    constexpr int nk = DM / 64;

    if (threadIdx.x == 0) {
        for (int i = 0; i < M1_STAGES; i++) { mbar_init(bar_full + 8 * i, 1); mbar_init(bar_empty + 8 * i, 4); }
        fence_barrier_init();
    }
    __syncthreads();

    if (wg == 0) {
        if (tid == 0) {
            for (int it = 0; it < nk; it++) {
                int s = it % M1_STAGES;
                uint32_t ph = (it / M1_STAGES) & 1;
                mbar_wait(bar_empty + 8 * s, ph ^ 1);
                mbar_expect_tx(bar_full + 8 * s, G_STAGE_BYTES);
                uint32_t a = sbase + s * G_STAGE_BYTES;
                tma_load_2d(a, &mapA, bar_full + 8 * s, it * 64, m0);
                tma_load_2d(a + 8192, &mapB, bar_full + 8 * s, n0, it * 64);
                tma_load_2d(a + 8192 + 8192, &mapB, bar_full + 8 * s, n0 + 64, it * 64);
            }
        }
    } else {
        float acc[64];
        int warp = tid >> 5, lane = tid & 31;
        for (int it = 0; it < nk; it++) {
            int s = it % M1_STAGES;
            uint32_t ph = (it / M1_STAGES) & 1;
            mbar_wait(bar_full + 8 * s, ph);
            uint32_t a = sbase + s * G_STAGE_BYTES;
            uint32_t b = a + 8192;
            wgmma_fence();
#pragma unroll
            for (int kk = 0; kk < 4; kk++)
                wgmma_m64n128k16_ss<0, 1>(acc, make_desc(a + kk * 32, 16, 1024), make_desc(b + kk * 2048, 8192, 1024), (it | kk) != 0);
            wgmma_commit();
            wgmma_wait<1>();
            if (it > 0 && lane == 0) mbar_arrive(bar_empty + 8 * ((it - 1) % M1_STAGES));
        }
        wgmma_wait<0>();
        int r = warp * 16 + (lane >> 2);
#pragma unroll
        for (int j = 0; j < 16; j++) {
            int c = n0 + j * 8 + (lane & 3) * 2;
            float b0 = 0.f, b1 = 0.f;
            if (c < FF) { b0 = __bfloat162float(bias[c]); b1 = __bfloat162float(bias[c + 1]); }
            uint32_t a = sbase + r * 256 + ((j ^ (r & 7)) << 4) + (lane & 3) * 4;
            st_shared_u32(a, pack_bf16(gelu_tanh(acc[j * 4 + 0] + b0), gelu_tanh(acc[j * 4 + 1] + b1)));
            st_shared_u32(a + 2048, pack_bf16(gelu_tanh(acc[j * 4 + 2] + b0), gelu_tanh(acc[j * 4 + 3] + b1)));
        }
        named_sync(1, 128);
#pragma unroll
        for (int i = 0; i < 8; i++) {
            int idx = i * 128 + tid;
            int rr = idx >> 4, ch = idx & 15;
            uint4 v = ld_shared_v4(sbase + rr * 256 + ((ch ^ (rr & 7)) << 4));
            if (n0 + ch * 8 < FF)
                *reinterpret_cast<uint4*>(C + (size_t)(m0 + rr) * FF + n0 + ch * 8) = v;
        }
    }
}

constexpr int A_KV_STAGES = 2;
constexpr int A_TILE_BYTES = 128 * 128 * 2;
constexpr int A_SMEM = A_TILE_BYTES * (1 + 2 * A_KV_STAGES) + 1024 + 256;

__global__ void __launch_bounds__(384, 1)
attn_kernel(const __grid_constant__ CUtensorMap mapXn, const __grid_constant__ CUtensorMap mapWq,
            const __grid_constant__ CUtensorMap mapK, const __grid_constant__ CUtensorMap mapV) {
    extern __shared__ uint8_t smem_raw[];
    uint32_t sbase = (smem_u32(smem_raw) + 1023) & ~1023u;
    uint32_t sQ = sbase;
    uint32_t sK = sQ + A_TILE_BYTES;
    uint32_t sV = sK + A_KV_STAGES * A_TILE_BYTES;
    uint32_t bars = sV + A_KV_STAGES * A_TILE_BYTES;
    uint32_t bar_pf = bars, bar_pe = bars + 32;
    uint32_t bar_kf = bars + 64, bar_ke = bar_kf + 8 * A_KV_STAGES;
    uint32_t bar_vf = bar_ke + 8 * A_KV_STAGES, bar_ve = bar_vf + 8 * A_KV_STAGES;
    int wg = threadIdx.x >> 7;
    int tid = threadIdx.x & 127;
    int qt = blockIdx.x, head = blockIdx.y;
    constexpr int NT = SEQ / 128;

    if (threadIdx.x == 0) {
        for (int i = 0; i < 4; i++) { mbar_init(bar_pf + 8 * i, 1); mbar_init(bar_pe + 8 * i, 8); }
        for (int i = 0; i < A_KV_STAGES; i++) {
            mbar_init(bar_kf + 8 * i, 1); mbar_init(bar_ke + 8 * i, 8);
            mbar_init(bar_vf + 8 * i, 1); mbar_init(bar_ve + 8 * i, 8);
        }
        fence_barrier_init();
    }
    __syncthreads();

    if (wg == 0) {
        reg_dealloc<40>();
        if (tid == 0) {
            for (int i = 0; i < 8; i++) {
                int b = i & 3;
                uint32_t buf = sK + b * A_TILE_BYTES;
                mbar_wait(bar_pe + 8 * b, ((i >> 2) & 1) ^ 1);
                mbar_expect_tx(bar_pf + 8 * b, A_TILE_BYTES);
                tma_load_2d(buf, &mapXn, bar_pf + 8 * b, i * 64, qt * 128);
                tma_load_2d(buf + 16384, &mapWq, bar_pf + 8 * b, head * DH, i * 64);
                tma_load_2d(buf + 16384 + 8192, &mapWq, bar_pf + 8 * b, head * DH + 64, i * 64);
            }
            for (int it = 0; it < NT; it++) {
                int s = it % A_KV_STAGES;
                uint32_t ph = (it / A_KV_STAGES) & 1;
                int row = head * SEQ + it * 128;
                if (it < A_KV_STAGES) mbar_wait(bar_pe + 8 * s, 1);
                else mbar_wait(bar_ke + 8 * s, ph ^ 1);
                mbar_expect_tx(bar_kf + 8 * s, A_TILE_BYTES);
                tma_load_2d(sK + s * A_TILE_BYTES, &mapK, bar_kf + 8 * s, 0, row);
                tma_load_2d(sK + s * A_TILE_BYTES + 16384, &mapK, bar_kf + 8 * s, 64, row);
                if (it < A_KV_STAGES) mbar_wait(bar_pe + 8 * (A_KV_STAGES + s), 1);
                else mbar_wait(bar_ve + 8 * s, ph ^ 1);
                mbar_expect_tx(bar_vf + 8 * s, A_TILE_BYTES);
                tma_load_2d(sV + s * A_TILE_BYTES, &mapV, bar_vf + 8 * s, 0, row);
                tma_load_2d(sV + s * A_TILE_BYTES + 16384, &mapV, bar_vf + 8 * s, 64, row);
            }
        }
    } else {
        reg_alloc<232>();
        int cw = wg - 1;
        int warp = tid >> 5, lane = tid & 31;
        float o[64];
        for (int i = 0; i < 8; i++) {
            int b = i & 3;
            uint32_t buf = sK + b * A_TILE_BYTES;
            mbar_wait(bar_pf + 8 * b, (i >> 2) & 1);
            wgmma_fence();
#pragma unroll
            for (int kk = 0; kk < 4; kk++)
                wgmma_m64n128k16_ss<0, 1>(o, make_desc(buf + cw * 8192 + kk * 32, 16, 1024),
                                          make_desc(buf + 16384 + kk * 2048, 8192, 1024), (i | kk) != 0);
            wgmma_commit();
            wgmma_wait<0>();
            if (lane == 0) mbar_arrive(bar_pe + 8 * b);
        }
        {
            int r = cw * 64 + warp * 16 + (lane >> 2);
#pragma unroll
            for (int j = 0; j < 16; j++) {
                uint32_t a = sQ + (j >> 3) * 16384 + r * 128 + (((j & 7) ^ (r & 7)) << 4) + (lane & 3) * 4;
                st_shared_u32(a, pack_bf16(o[j * 4 + 0], o[j * 4 + 1]));
                st_shared_u32(a + 1024, pack_bf16(o[j * 4 + 2], o[j * 4 + 3]));
            }
            fence_proxy_async();
            named_sync(3 + cw, 128);
        }
#pragma unroll
        for (int i = 0; i < 64; i++) o[i] = 0.f;
        float m0 = -INFINITY, m1 = -INFINITY, l0 = 0.f, l1 = 0.f;
        const float sc = 0.08838834764831845f * 1.4426950408889634f;
        if (cw == 1) named_arrive(1, 256);
        uint32_t qa = sQ + cw * 8192;
        float sacc[64];
        uint32_t p[32];
        mbar_wait(bar_kf, 0);
        named_sync(1 + cw, 256);
        wgmma_fence();
#pragma unroll
        for (int kk = 0; kk < 8; kk++) {
            uint32_t off = (kk >> 2) * 16384 + (kk & 3) * 32;
            wgmma_m64n128k16_ss<0, 0>(sacc, make_desc(qa + off, 16, 1024), make_desc(sK + off, 16, 1024), kk != 0);
        }
        wgmma_commit();
        named_arrive(1 + (cw ^ 1), 256);
        wgmma_wait<0>();
        if (lane == 0) mbar_arrive(bar_ke);
        {
            float mx0 = -INFINITY, mx1 = -INFINITY;
#pragma unroll
            for (int j = 0; j < 16; j++) {
                mx0 = fmaxf(mx0, fmaxf(sacc[j * 4 + 0], sacc[j * 4 + 1]));
                mx1 = fmaxf(mx1, fmaxf(sacc[j * 4 + 2], sacc[j * 4 + 3]));
            }
            mx0 = fmaxf(mx0, __shfl_xor_sync(0xffffffffu, mx0, 1));
            mx0 = fmaxf(mx0, __shfl_xor_sync(0xffffffffu, mx0, 2));
            mx1 = fmaxf(mx1, __shfl_xor_sync(0xffffffffu, mx1, 1));
            mx1 = fmaxf(mx1, __shfl_xor_sync(0xffffffffu, mx1, 2));
            m0 = mx0; m1 = mx1;
            float ms0 = mx0 * sc, ms1 = mx1 * sc;
#pragma unroll
            for (int j = 0; j < 16; j++) {
                float p0 = fast_exp2(sacc[j * 4 + 0] * sc - ms0);
                float p1 = fast_exp2(sacc[j * 4 + 1] * sc - ms0);
                float p2 = fast_exp2(sacc[j * 4 + 2] * sc - ms1);
                float p3 = fast_exp2(sacc[j * 4 + 3] * sc - ms1);
                l0 += p0 + p1; l1 += p2 + p3;
                p[j * 2 + 0] = pack_bf16(p0, p1);
                p[j * 2 + 1] = pack_bf16(p2, p3);
            }
        }
        for (int it = 1; it < NT; it++) {
            int s = it % A_KV_STAGES;
            uint32_t ph = (it / A_KV_STAGES) & 1;
            int sp = (it - 1) % A_KV_STAGES;
            uint32_t php = ((it - 1) / A_KV_STAGES) & 1;
            mbar_wait(bar_kf + 8 * s, ph);
            named_sync(1 + cw, 256);
            uint32_t kb = sK + s * A_TILE_BYTES;
            wgmma_fence();
#pragma unroll
            for (int kk = 0; kk < 8; kk++) {
                uint32_t off = (kk >> 2) * 16384 + (kk & 3) * 32;
                wgmma_m64n128k16_ss<0, 0>(sacc, make_desc(qa + off, 16, 1024), make_desc(kb + off, 16, 1024), kk != 0);
            }
            wgmma_commit();
            mbar_wait(bar_vf + 8 * sp, php);
            uint32_t vb = sV + sp * A_TILE_BYTES;
#pragma unroll
            for (int kk = 0; kk < 8; kk++) {
                wgmma_m64n128k16_rs<1>(o, p[kk * 4 + 0], p[kk * 4 + 1], p[kk * 4 + 2], p[kk * 4 + 3],
                                       make_desc(vb + kk * 2048, 16384, 1024), 1);
            }
            wgmma_commit();
            named_arrive(1 + (cw ^ 1), 256);
            wgmma_wait<1>();
            if (lane == 0) mbar_arrive(bar_ke + 8 * s);
            float mx0 = m0, mx1 = m1;
#pragma unroll
            for (int j = 0; j < 16; j++) {
                mx0 = fmaxf(mx0, fmaxf(sacc[j * 4 + 0], sacc[j * 4 + 1]));
                mx1 = fmaxf(mx1, fmaxf(sacc[j * 4 + 2], sacc[j * 4 + 3]));
            }
            mx0 = fmaxf(mx0, __shfl_xor_sync(0xffffffffu, mx0, 1));
            mx0 = fmaxf(mx0, __shfl_xor_sync(0xffffffffu, mx0, 2));
            mx1 = fmaxf(mx1, __shfl_xor_sync(0xffffffffu, mx1, 1));
            mx1 = fmaxf(mx1, __shfl_xor_sync(0xffffffffu, mx1, 2));
            float c0 = fast_exp2((m0 - mx0) * sc), c1 = fast_exp2((m1 - mx1) * sc);
            m0 = mx0; m1 = mx1;
            float ms0 = mx0 * sc, ms1 = mx1 * sc;
            float rs0 = 0.f, rs1 = 0.f;
#pragma unroll
            for (int j = 0; j < 16; j++) {
                sacc[j * 4 + 0] = fast_exp2(sacc[j * 4 + 0] * sc - ms0);
                sacc[j * 4 + 1] = fast_exp2(sacc[j * 4 + 1] * sc - ms0);
                sacc[j * 4 + 2] = fast_exp2(sacc[j * 4 + 2] * sc - ms1);
                sacc[j * 4 + 3] = fast_exp2(sacc[j * 4 + 3] * sc - ms1);
                rs0 += sacc[j * 4 + 0] + sacc[j * 4 + 1]; rs1 += sacc[j * 4 + 2] + sacc[j * 4 + 3];
            }
            l0 = l0 * c0 + rs0; l1 = l1 * c1 + rs1;
            wgmma_wait<0>();
            if (lane == 0) mbar_arrive(bar_ve + 8 * sp);
#pragma unroll
            for (int j = 0; j < 16; j++) {
                o[j * 4 + 0] *= c0; o[j * 4 + 1] *= c0; o[j * 4 + 2] *= c1; o[j * 4 + 3] *= c1;
                p[j * 2 + 0] = pack_bf16(sacc[j * 4 + 0], sacc[j * 4 + 1]);
                p[j * 2 + 1] = pack_bf16(sacc[j * 4 + 2], sacc[j * 4 + 3]);
            }
        }
        {
            int sp = (NT - 1) % A_KV_STAGES;
            uint32_t php = ((NT - 1) / A_KV_STAGES) & 1;
            mbar_wait(bar_vf + 8 * sp, php);
            uint32_t vb = sV + sp * A_TILE_BYTES;
            wgmma_fence();
#pragma unroll
            for (int kk = 0; kk < 8; kk++) {
                wgmma_m64n128k16_rs<1>(o, p[kk * 4 + 0], p[kk * 4 + 1], p[kk * 4 + 2], p[kk * 4 + 3],
                                       make_desc(vb + kk * 2048, 16384, 1024), 1);
            }
            wgmma_commit();
            wgmma_wait<0>();
        }
        l0 += __shfl_xor_sync(0xffffffffu, l0, 1);
        l0 += __shfl_xor_sync(0xffffffffu, l0, 2);
        l1 += __shfl_xor_sync(0xffffffffu, l1, 1);
        l1 += __shfl_xor_sync(0xffffffffu, l1, 2);
        float i0 = 1.f / l0, i1 = 1.f / l1;
        {
            int r = cw * 64 + warp * 16 + (lane >> 2);
#pragma unroll
            for (int j = 0; j < 16; j++) {
                uint32_t a = sQ + (j >> 3) * 16384 + r * 128 + (((j & 7) ^ (r & 7)) << 4) + (lane & 3) * 4;
                st_shared_u32(a, pack_bf16(o[j * 4 + 0] * i0, o[j * 4 + 1] * i0));
                st_shared_u32(a + 1024, pack_bf16(o[j * 4 + 2] * i1, o[j * 4 + 3] * i1));
            }
            named_sync(3 + cw, 128);
#pragma unroll
            for (int i = 0; i < 8; i++) {
                int idx = i * 128 + tid;
                int rr = cw * 64 + (idx >> 4), ch = idx & 15;
                uint32_t a = sQ + (ch >> 3) * 16384 + rr * 128 + (((ch & 7) ^ (rr & 7)) << 4);
                uint4 v = ld_shared_v4(a);
                *reinterpret_cast<uint4*>(g_o + (size_t)(qt * 128 + rr) * HD + head * DH + ch * 8) = v;
            }
        }
    }
}

constexpr int F_STAGES = 8;
constexpr int F_SMEM = F_STAGES * G_STAGE_BYTES + 1024 + 256;
__global__ void __launch_bounds__(256, 1)
final_kernel(const __grid_constant__ CUtensorMap mapO, const __grid_constant__ CUtensorMap mapWo,
             const __grid_constant__ CUtensorMap mapH, const __grid_constant__ CUtensorMap mapW2,
             const bf16* __restrict__ x, const bf16* __restrict__ b2, bf16* __restrict__ out) {
    extern __shared__ uint8_t smem_raw[];
    uint32_t sbase = (smem_u32(smem_raw) + 1023) & ~1023u;
    uint32_t bar_full = sbase + F_STAGES * G_STAGE_BYTES;
    uint32_t bar_empty = bar_full + 8 * F_STAGES;
    int wg = threadIdx.x >> 7;
    int tid = threadIdx.x & 127;
    int m0 = blockIdx.y * 64, n0 = blockIdx.x * 128;
    constexpr int NK1 = HD / 64;
    constexpr int NK2 = (FF + 63) / 64;

    if (threadIdx.x == 0) {
        for (int i = 0; i < F_STAGES; i++) { mbar_init(bar_full + 8 * i, 1); mbar_init(bar_empty + 8 * i, 4); }
        fence_barrier_init();
    }
    __syncthreads();

    if (wg == 0) {
        if (tid == 0) {
            for (int it = 0; it < NK1 + NK2; it++) {
                int s = it % F_STAGES;
                uint32_t ph = (it / F_STAGES) & 1;
                mbar_wait(bar_empty + 8 * s, ph ^ 1);
                mbar_expect_tx(bar_full + 8 * s, G_STAGE_BYTES);
                uint32_t a = sbase + s * G_STAGE_BYTES;
                const CUtensorMap* pa = it < NK2 ? &mapH : &mapO;
                const CUtensorMap* pb = it < NK2 ? &mapW2 : &mapWo;
                int k = (it < NK2 ? it : it - NK2) * 64;
                tma_load_2d(a, pa, bar_full + 8 * s, k, m0);
                tma_load_2d(a + 8192, pb, bar_full + 8 * s, n0, k);
                tma_load_2d(a + 8192 + 8192, pb, bar_full + 8 * s, n0 + 64, k);
            }
        }
    } else {
        float acc[64], acc2[64];
        int warp = tid >> 5, lane = tid & 31;
        for (int it = 0; it < NK2; it++) {
            int s = it % F_STAGES;
            uint32_t ph = (it / F_STAGES) & 1;
            mbar_wait(bar_full + 8 * s, ph);
            uint32_t a = sbase + s * G_STAGE_BYTES;
            uint32_t b = a + 8192;
            wgmma_fence();
#pragma unroll
            for (int kk = 0; kk < 4; kk++)
                wgmma_m64n128k16_ss<0, 1>(acc2, make_desc(a + kk * 32, 16, 1024), make_desc(b + kk * 2048, 8192, 1024), (it | kk) != 0);
            wgmma_commit();
            wgmma_wait<1>();
            if (it > 0 && lane == 0) mbar_arrive(bar_empty + 8 * ((it - 1) % F_STAGES));
        }
        for (int it = NK2; it < NK1 + NK2; it++) {
            int s = it % F_STAGES;
            uint32_t ph = (it / F_STAGES) & 1;
            mbar_wait(bar_full + 8 * s, ph);
            uint32_t a = sbase + s * G_STAGE_BYTES;
            uint32_t b = a + 8192;
            wgmma_fence();
#pragma unroll
            for (int kk = 0; kk < 4; kk++)
                wgmma_m64n128k16_ss<0, 1>(acc, make_desc(a + kk * 32, 16, 1024), make_desc(b + kk * 2048, 8192, 1024), ((it - NK2) | kk) != 0);
            wgmma_commit();
            wgmma_wait<1>();
            if (lane == 0) mbar_arrive(bar_empty + 8 * ((it - 1) % F_STAGES));
        }
        wgmma_wait<0>();
        int r = warp * 16 + (lane >> 2);
#pragma unroll
        for (int j = 0; j < 16; j++) {
            int c = n0 + j * 8 + (lane & 3) * 2;
            float b0 = __bfloat162float(b2[c]), b1 = __bfloat162float(b2[c + 1]);
            uint32_t a = sbase + r * 256 + ((j ^ (r & 7)) << 4) + (lane & 3) * 4;
#pragma unroll
            for (int h = 0; h < 2; h++) {
                float2 xv = __bfloat1622float2(*reinterpret_cast<const __nv_bfloat162*>(x + (size_t)(m0 + r + h * 8) * DM + c));
                float g0 = acc2[j * 4 + h * 2 + 0] + b0, g1 = acc2[j * 4 + h * 2 + 1] + b1;
                g0 = g0 / (1.f + __expf(-g0)); g1 = g1 / (1.f + __expf(-g1));
                st_shared_u32(a + h * 2048, pack_bf16(xv.x + acc[j * 4 + h * 2 + 0] * g0, xv.y + acc[j * 4 + h * 2 + 1] * g1));
            }
        }
        named_sync(1, 128);
#pragma unroll
        for (int i = 0; i < 8; i++) {
            int idx = i * 128 + tid;
            int rr = idx >> 4, ch = idx & 15;
            uint4 v = ld_shared_v4(sbase + rr * 256 + ((ch ^ (rr & 7)) << 4));
            *reinterpret_cast<uint4*>(out + (size_t)(m0 + rr) * DM + n0 + ch * 8) = v;
        }
    }
}

typedef CUresult (*EncodeFn)(CUtensorMap*, CUtensorMapDataType, cuuint32_t, void*, const cuuint64_t*, const cuuint64_t*,
                             const cuuint32_t*, const cuuint32_t*, CUtensorMapInterleave, CUtensorMapSwizzle,
                             CUtensorMapL2promotion, CUtensorMapFloatOOBfill);

static void make_map(EncodeFn fn, CUtensorMap* m, const void* ptr, uint64_t inner, uint64_t outer,
                     uint32_t box_inner, uint32_t box_outer) {
    cuuint64_t dims[2] = {inner, outer};
    cuuint64_t strides[1] = {inner * 2};
    cuuint32_t box[2] = {box_inner, box_outer};
    cuuint32_t es[2] = {1, 1};
    fn(m, CU_TENSOR_MAP_DATA_TYPE_BFLOAT16, 2, const_cast<void*>(ptr), dims, strides, box, es,
       CU_TENSOR_MAP_INTERLEAVE_NONE, CU_TENSOR_MAP_SWIZZLE_128B, CU_TENSOR_MAP_L2_PROMOTION_L2_256B,
       CU_TENSOR_MAP_FLOAT_OOB_FILL_NONE);
}

extern "C" void kernel_launch(void* const* d_in, const int* in_sizes, int n_in, void* d_out, int out_size) {
    const bf16* x  = (const bf16*)d_in[0];
    const bf16* kc = (const bf16*)d_in[1];
    const bf16* vc = (const bf16*)d_in[2];
    const bf16* wq = (const bf16*)d_in[3];
    const bf16* wo = (const bf16*)d_in[4];
    const bf16* w1 = (const bf16*)d_in[6];
    const bf16* b1 = (const bf16*)d_in[7];
    const bf16* w2 = (const bf16*)d_in[8];
    const bf16* b2 = (const bf16*)d_in[9];
    bf16* out = (bf16*)d_out;

    static bool inited = false;
    static CUtensorMap mXn, mY, mWq, mW1, mQ, mK, mV, mO, mWo, mH, mW2;
    static void *pq, *ph;
    if (!inited) {
        EncodeFn fn = nullptr;
        cudaDriverEntryPointQueryResult qres;
        cudaGetDriverEntryPoint("cuTensorMapEncodeTiled", (void**)&fn, cudaEnableDefault, &qres);
        void *pxn, *py, *po;
        cudaGetSymbolAddress(&pxn, g_xn); cudaGetSymbolAddress(&py, g_y); cudaGetSymbolAddress(&pq, g_q);
        cudaGetSymbolAddress(&ph, g_h); cudaGetSymbolAddress(&po, g_o);
        make_map(fn, &mXn, pxn, DM, SEQ, 64, 128);
        make_map(fn, &mY, py, DM, SEQ, 64, 64);
        make_map(fn, &mWq, wq, HD, DM, 64, 64);
        make_map(fn, &mW1, w1, FF, DM, 64, 64);
        make_map(fn, &mK, kc, DH, NH * SEQ, 64, 128);
        make_map(fn, &mV, vc, DH, NH * SEQ, 64, 128);
        make_map(fn, &mO, po, HD, SEQ, 64, 64);
        make_map(fn, &mWo, wo, DM, HD, 64, 64);
        make_map(fn, &mH, ph, FF, SEQ, 64, 64);
        make_map(fn, &mW2, w2, DM, FF, 64, 64);
        cudaFuncSetAttribute(mlp1_kernel, cudaFuncAttributeMaxDynamicSharedMemorySize, M1_SMEM);
        cudaFuncSetAttribute(final_kernel, cudaFuncAttributeMaxDynamicSharedMemorySize, F_SMEM);
        cudaFuncSetAttribute(attn_kernel, cudaFuncAttributeMaxDynamicSharedMemorySize, A_SMEM);
        inited = true;
    }

    ln_kernel<<<SEQ / 8, 256>>>(x);
    mlp1_kernel<<<dim3((FF + 127) / 128, SEQ / 64), 256, M1_SMEM>>>(mY, mW1, (bf16*)ph, b1);
    attn_kernel<<<dim3(SEQ / 128, NH), 384, A_SMEM>>>(mXn, mWq, mK, mV);
    final_kernel<<<dim3(DM / 128, SEQ / 64), 256, F_SMEM>>>(mO, mWo, mH, mW2, x, b2, out);
}
```

```cpp
#include <cuda_runtime.h>
#include <cuda_bf16.h>
#include <cuda.h>
#include <stdint.h>

typedef __nv_bfloat16 bf16;

constexpr int SEQ = 2048;
constexpr int DM  = 512;
constexpr int NH  = 32;
constexpr int DH  = 128;
constexpr int HD  = NH * DH;
constexpr int FF  = 1376;

__device__ bf16 g_xn[SEQ * DM];
__device__ bf16 g_y [SEQ * DM];
__device__ bf16 g_q [SEQ * HD];
__device__ bf16 g_h [SEQ * FF];
__device__ bf16 g_o [SEQ * HD];

__device__ __forceinline__ uint32_t smem_u32(const void* p) {
    return (uint32_t)__cvta_generic_to_shared(p);
}
__device__ __forceinline__ void mbar_init(uint32_t bar, uint32_t count) {
    asm volatile("mbarrier.init.shared::cta.b64 [%0], %1;" :: "r"(bar), "r"(count) : "memory");
}
__device__ __forceinline__ void mbar_arrive(uint32_t bar) {
    asm volatile("mbarrier.arrive.shared::cta.b64 _, [%0];" :: "r"(bar) : "memory");
}
__device__ __forceinline__ void mbar_expect_tx(uint32_t bar, uint32_t bytes) {
    asm volatile("mbarrier.arrive.expect_tx.shared::cta.b64 _, [%0], %1;" :: "r"(bar), "r"(bytes) : "memory");
}
__device__ __forceinline__ void mbar_wait(uint32_t bar, uint32_t parity) {
    asm volatile(
        "{\n"
        ".reg .pred p;\n"
        "LAB_WAIT:\n"
        "mbarrier.try_wait.parity.shared::cta.b64 p, [%0], %1;\n"
        "@p bra DONE;\n"
        "bra LAB_WAIT;\n"
        "DONE:\n"
        "}\n" :: "r"(bar), "r"(parity) : "memory");
}
__device__ __forceinline__ void tma_load_2d(uint32_t dst, const CUtensorMap* map, uint32_t bar, int c0, int c1) {
    asm volatile(
        "cp.async.bulk.tensor.2d.shared::cluster.global.mbarrier::complete_tx::bytes [%0], [%1, {%3, %4}], [%2];"
        :: "r"(dst), "l"((uint64_t)map), "r"(bar), "r"(c0), "r"(c1) : "memory");
}
__device__ __forceinline__ void wgmma_fence() { asm volatile("wgmma.fence.sync.aligned;" ::: "memory"); }
__device__ __forceinline__ void wgmma_commit() { asm volatile("wgmma.commit_group.sync.aligned;" ::: "memory"); }
template <int N> __device__ __forceinline__ void wgmma_wait() {
    asm volatile("wgmma.wait_group.sync.aligned %0;" :: "n"(N) : "memory");
}
template <int R> __device__ __forceinline__ void reg_alloc() {
    asm volatile("setmaxnreg.inc.sync.aligned.u32 %0;" :: "n"(R));
}
template <int R> __device__ __forceinline__ void reg_dealloc() {
    asm volatile("setmaxnreg.dec.sync.aligned.u32 %0;" :: "n"(R));
}
__device__ __forceinline__ void fence_barrier_init() {
    asm volatile("fence.mbarrier_init.release.cluster;" ::: "memory");
}
__device__ __forceinline__ void fence_proxy_async() {
    asm volatile("fence.proxy.async.shared::cta;" ::: "memory");
}

__device__ __forceinline__ void named_sync(int id, int n) {
    asm volatile("bar.sync %0, %1;" :: "r"(id), "r"(n) : "memory");
}
__device__ __forceinline__ void named_arrive(int id, int n) {
    asm volatile("bar.arrive %0, %1;" :: "r"(id), "r"(n) : "memory");
}
__device__ __forceinline__ float fast_exp2(float x) {
    float y;
    asm("ex2.approx.ftz.f32 %0, %1;" : "=f"(y) : "f"(x));
    return y;
}

__device__ __forceinline__ void st_shared_u32(uint32_t a, uint32_t v) {
    asm volatile("st.shared.u32 [%0], %1;" :: "r"(a), "r"(v) : "memory");
}
__device__ __forceinline__ uint4 ld_shared_v4(uint32_t a) {
    uint4 v;
    asm volatile("ld.shared.v4.u32 {%0,%1,%2,%3}, [%4];" : "=r"(v.x), "=r"(v.y), "=r"(v.z), "=r"(v.w) : "r"(a) : "memory");
    return v;
}

__device__ __forceinline__ uint64_t make_desc(uint32_t addr, uint32_t lbo_bytes, uint32_t sbo_bytes) {
    uint64_t d = 0;
    d |= (uint64_t)((addr & 0x3FFFF) >> 4);
    d |= (uint64_t)((lbo_bytes & 0x3FFFF) >> 4) << 16;
    d |= (uint64_t)((sbo_bytes & 0x3FFFF) >> 4) << 32;
    d |= (uint64_t)1 << 62;
    return d;
}

template <int TA, int TB>
__device__ __forceinline__ void wgmma_m64n128k16_ss(float (&d)[64], uint64_t da, uint64_t db, int scale_d) {
    asm volatile(
        "{\n.reg .pred p;\nsetp.ne.b32 p, %66, 0;\n"
        "wgmma.mma_async.sync.aligned.m64n128k16.f32.bf16.bf16 "
        "{%0,%1,%2,%3,%4,%5,%6,%7,%8,%9,%10,%11,%12,%13,%14,%15,"
        "%16,%17,%18,%19,%20,%21,%22,%23,%24,%25,%26,%27,%28,%29,%30,%31,"
        "%32,%33,%34,%35,%36,%37,%38,%39,%40,%41,%42,%43,%44,%45,%46,%47,"
        "%48,%49,%50,%51,%52,%53,%54,%55,%56,%57,%58,%59,%60,%61,%62,%63},"
        " %64, %65, p, 1, 1, %67, %68;\n}\n"
        : "+f"(d[0]), "+f"(d[1]), "+f"(d[2]), "+f"(d[3]), "+f"(d[4]), "+f"(d[5]), "+f"(d[6]), "+f"(d[7]),
          "+f"(d[8]), "+f"(d[9]), "+f"(d[10]), "+f"(d[11]), "+f"(d[12]), "+f"(d[13]), "+f"(d[14]), "+f"(d[15]),
          "+f"(d[16]), "+f"(d[17]), "+f"(d[18]), "+f"(d[19]), "+f"(d[20]), "+f"(d[21]), "+f"(d[22]), "+f"(d[23]),
          "+f"(d[24]), "+f"(d[25]), "+f"(d[26]), "+f"(d[27]), "+f"(d[28]), "+f"(d[29]), "+f"(d[30]), "+f"(d[31]),
          "+f"(d[32]), "+f"(d[33]), "+f"(d[34]), "+f"(d[35]), "+f"(d[36]), "+f"(d[37]), "+f"(d[38]), "+f"(d[39]),
          "+f"(d[40]), "+f"(d[41]), "+f"(d[42]), "+f"(d[43]), "+f"(d[44]), "+f"(d[45]), "+f"(d[46]), "+f"(d[47]),
          "+f"(d[48]), "+f"(d[49]), "+f"(d[50]), "+f"(d[51]), "+f"(d[52]), "+f"(d[53]), "+f"(d[54]), "+f"(d[55]),
          "+f"(d[56]), "+f"(d[57]), "+f"(d[58]), "+f"(d[59]), "+f"(d[60]), "+f"(d[61]), "+f"(d[62]), "+f"(d[63])
        : "l"(da), "l"(db), "r"(scale_d), "n"(TA), "n"(TB));
}

template <int TB>
__device__ __forceinline__ void wgmma_m64n128k16_rs(float (&d)[64], uint32_t a0, uint32_t a1, uint32_t a2, uint32_t a3,
                                                    uint64_t db, int scale_d) {
    asm volatile(
        "{\n.reg .pred p;\nsetp.ne.b32 p, %69, 0;\n"
        "wgmma.mma_async.sync.aligned.m64n128k16.f32.bf16.bf16 "
        "{%0,%1,%2,%3,%4,%5,%6,%7,%8,%9,%10,%11,%12,%13,%14,%15,"
        "%16,%17,%18,%19,%20,%21,%22,%23,%24,%25,%26,%27,%28,%29,%30,%31,"
        "%32,%33,%34,%35,%36,%37,%38,%39,%40,%41,%42,%43,%44,%45,%46,%47,"
        "%48,%49,%50,%51,%52,%53,%54,%55,%56,%57,%58,%59,%60,%61,%62,%63},"
        " {%64,%65,%66,%67}, %68, p, 1, 1, %70;\n}\n"
        : "+f"(d[0]), "+f"(d[1]), "+f"(d[2]), "+f"(d[3]), "+f"(d[4]), "+f"(d[5]), "+f"(d[6]), "+f"(d[7]),
          "+f"(d[8]), "+f"(d[9]), "+f"(d[10]), "+f"(d[11]), "+f"(d[12]), "+f"(d[13]), "+f"(d[14]), "+f"(d[15]),
          "+f"(d[16]), "+f"(d[17]), "+f"(d[18]), "+f"(d[19]), "+f"(d[20]), "+f"(d[21]), "+f"(d[22]), "+f"(d[23]),
          "+f"(d[24]), "+f"(d[25]), "+f"(d[26]), "+f"(d[27]), "+f"(d[28]), "+f"(d[29]), "+f"(d[30]), "+f"(d[31]),
          "+f"(d[32]), "+f"(d[33]), "+f"(d[34]), "+f"(d[35]), "+f"(d[36]), "+f"(d[37]), "+f"(d[38]), "+f"(d[39]),
          "+f"(d[40]), "+f"(d[41]), "+f"(d[42]), "+f"(d[43]), "+f"(d[44]), "+f"(d[45]), "+f"(d[46]), "+f"(d[47]),
          "+f"(d[48]), "+f"(d[49]), "+f"(d[50]), "+f"(d[51]), "+f"(d[52]), "+f"(d[53]), "+f"(d[54]), "+f"(d[55]),
          "+f"(d[56]), "+f"(d[57]), "+f"(d[58]), "+f"(d[59]), "+f"(d[60]), "+f"(d[61]), "+f"(d[62]), "+f"(d[63])
        : "r"(a0), "r"(a1), "r"(a2), "r"(a3), "l"(db), "r"(scale_d), "n"(TB));
}

__device__ __forceinline__ uint32_t pack_bf16(float lo, float hi) {
    __nv_bfloat162 v = __floats2bfloat162_rn(lo, hi);
    return *reinterpret_cast<uint32_t*>(&v);
}

__global__ void __launch_bounds__(256) ln_kernel(const bf16* __restrict__ x) {
    int warp = threadIdx.x >> 5, lane = threadIdx.x & 31;
    int row = blockIdx.x * 8 + warp;
    const uint4* src = reinterpret_cast<const uint4*>(x + (size_t)row * DM);
    float v[16];
#pragma unroll
    for (int i = 0; i < 2; i++) {
        uint4 u = src[lane + i * 32];
        const __nv_bfloat162* h = reinterpret_cast<const __nv_bfloat162*>(&u);
#pragma unroll
        for (int j = 0; j < 4; j++) {
            float2 f = __bfloat1622float2(h[j]);
            v[i * 8 + j * 2] = f.x; v[i * 8 + j * 2 + 1] = f.y;
        }
    }
#pragma unroll
    for (int pass = 0; pass < 2; pass++) {
        float s = 0.f;
#pragma unroll
        for (int i = 0; i < 16; i++) s += v[i];
#pragma unroll
        for (int o = 16; o > 0; o >>= 1) s += __shfl_xor_sync(0xffffffffu, s, o);
        float mean = s * (1.f / DM);
        float q = 0.f;
#pragma unroll
        for (int i = 0; i < 16; i++) { float d = v[i] - mean; q += d * d; }
#pragma unroll
        for (int o = 16; o > 0; o >>= 1) q += __shfl_xor_sync(0xffffffffu, q, o);
        float rstd = 1.0f / sqrtf(q * (1.f / DM) + 1e-5f);
        bf16* dst = (pass == 0 ? g_xn : g_y) + (size_t)row * DM;
#pragma unroll
        for (int i = 0; i < 2; i++) {
            uint4 u;
            uint32_t* w = reinterpret_cast<uint32_t*>(&u);
#pragma unroll
            for (int j = 0; j < 4; j++) {
                __nv_bfloat162 h = __floats2bfloat162_rn((v[i * 8 + j * 2] - mean) * rstd, (v[i * 8 + j * 2 + 1] - mean) * rstd);
                w[j] = *reinterpret_cast<uint32_t*>(&h);
                float2 f = __bfloat1622float2(h);
                v[i * 8 + j * 2] = f.x; v[i * 8 + j * 2 + 1] = f.y;
            }
            reinterpret_cast<uint4*>(dst)[lane + i * 32] = u;
        }
    }
}

constexpr int G_STAGE_BYTES = 8192 + 16384;

__device__ __forceinline__ float gelu_tanh(float x) {
    float u = 0.7978845608028654f * (x + 0.044715f * x * x * x);
    float t = 1.f - __fdividef(2.f, 1.f + __expf(2.f * u));
    return 0.5f * x * (1.f + t);
}

constexpr int M1_STAGES = 4;
constexpr int M1_SMEM = M1_STAGES * G_STAGE_BYTES + 1024 + 256;
__global__ void __launch_bounds__(256, 2)
mlp1_kernel(const __grid_constant__ CUtensorMap mapA, const __grid_constant__ CUtensorMap mapB,
            bf16* __restrict__ C, const bf16* __restrict__ bias) {
    extern __shared__ uint8_t smem_raw[];
    uint32_t sbase = (smem_u32(smem_raw) + 1023) & ~1023u;
    uint32_t bar_full = sbase + M1_STAGES * G_STAGE_BYTES;
    uint32_t bar_empty = bar_full + 8 * M1_STAGES;
    int wg = threadIdx.x >> 7;
    int tid = threadIdx.x & 127;
    int m0 = blockIdx.y * 64, n0 = blockIdx.x * 128;
    constexpr int nk = DM / 64;

    if (threadIdx.x == 0) {
        for (int i = 0; i < M1_STAGES; i++) { mbar_init(bar_full + 8 * i, 1); mbar_init(bar_empty + 8 * i, 4); }
        fence_barrier_init();
    }
    __syncthreads();

    if (wg == 0) {
        if (tid == 0) {
            for (int it = 0; it < nk; it++) {
                int s = it % M1_STAGES;
                uint32_t ph = (it / M1_STAGES) & 1;
                mbar_wait(bar_empty + 8 * s, ph ^ 1);
                mbar_expect_tx(bar_full + 8 * s, G_STAGE_BYTES);
                uint32_t a = sbase + s * G_STAGE_BYTES;
                tma_load_2d(a, &mapA, bar_full + 8 * s, it * 64, m0);
                tma_load_2d(a + 8192, &mapB, bar_full + 8 * s, n0, it * 64);
                tma_load_2d(a + 8192 + 8192, &mapB, bar_full + 8 * s, n0 + 64, it * 64);
            }
        }
    } else {
        float acc[64];
        int warp = tid >> 5, lane = tid & 31;
        uint32_t bv[16];
#pragma unroll
        for (int j = 0; j < 16; j++) {
            int c = min(n0 + j * 8 + (lane & 3) * 2, FF - 2);
            bv[j] = *reinterpret_cast<const uint32_t*>(bias + c);
        }
        for (int it = 0; it < nk; it++) {
            int s = it % M1_STAGES;
            uint32_t ph = (it / M1_STAGES) & 1;
            mbar_wait(bar_full + 8 * s, ph);
            uint32_t a = sbase + s * G_STAGE_BYTES;
            uint32_t b = a + 8192;
            wgmma_fence();
#pragma unroll
            for (int kk = 0; kk < 4; kk++)
                wgmma_m64n128k16_ss<0, 1>(acc, make_desc(a + kk * 32, 16, 1024), make_desc(b + kk * 2048, 8192, 1024), (it | kk) != 0);
            wgmma_commit();
            wgmma_wait<1>();
            if (it > 0 && lane == 0) mbar_arrive(bar_empty + 8 * ((it - 1) % M1_STAGES));
        }
        wgmma_wait<0>();
        int r = warp * 16 + (lane >> 2);
#pragma unroll
        for (int j = 0; j < 16; j++) {
            float2 bf = __bfloat1622float2(*reinterpret_cast<const __nv_bfloat162*>(&bv[j]));
            float b0 = bf.x, b1 = bf.y;
            uint32_t a = sbase + r * 256 + ((j ^ (r & 7)) << 4) + (lane & 3) * 4;
            st_shared_u32(a, pack_bf16(gelu_tanh(acc[j * 4 + 0] + b0), gelu_tanh(acc[j * 4 + 1] + b1)));
            st_shared_u32(a + 2048, pack_bf16(gelu_tanh(acc[j * 4 + 2] + b0), gelu_tanh(acc[j * 4 + 3] + b1)));
        }
        named_sync(1, 128);
#pragma unroll
        for (int i = 0; i < 8; i++) {
            int idx = i * 128 + tid;
            int rr = idx >> 4, ch = idx & 15;
            uint4 v = ld_shared_v4(sbase + rr * 256 + ((ch ^ (rr & 7)) << 4));
            if (n0 + ch * 8 < FF)
                *reinterpret_cast<uint4*>(C + (size_t)(m0 + rr) * FF + n0 + ch * 8) = v;
        }
    }
}

constexpr int A_KV_STAGES = 2;
constexpr int A_TILE_BYTES = 128 * 128 * 2;
constexpr int A_SMEM = A_TILE_BYTES * (1 + 2 * A_KV_STAGES) + 1024 + 256;

__global__ void __launch_bounds__(384, 1)
attn_kernel(const __grid_constant__ CUtensorMap mapXn, const __grid_constant__ CUtensorMap mapWq,
            const __grid_constant__ CUtensorMap mapK, const __grid_constant__ CUtensorMap mapV) {
    extern __shared__ uint8_t smem_raw[];
    uint32_t sbase = (smem_u32(smem_raw) + 1023) & ~1023u;
    uint32_t sQ = sbase;
    uint32_t sK = sQ + A_TILE_BYTES;
    uint32_t sV = sK + A_KV_STAGES * A_TILE_BYTES;
    uint32_t bars = sV + A_KV_STAGES * A_TILE_BYTES;
    uint32_t bar_pf = bars, bar_pe = bars + 32;
    uint32_t bar_kf = bars + 64, bar_ke = bar_kf + 8 * A_KV_STAGES;
    uint32_t bar_vf = bar_ke + 8 * A_KV_STAGES, bar_ve = bar_vf + 8 * A_KV_STAGES;
    int wg = threadIdx.x >> 7;
    int tid = threadIdx.x & 127;
    int qt = blockIdx.x, head = blockIdx.y;
    constexpr int NT = SEQ / 128;

    if (threadIdx.x == 0) {
        for (int i = 0; i < 4; i++) { mbar_init(bar_pf + 8 * i, 1); mbar_init(bar_pe + 8 * i, 8); }
        for (int i = 0; i < A_KV_STAGES; i++) {
            mbar_init(bar_kf + 8 * i, 1); mbar_init(bar_ke + 8 * i, 8);
            mbar_init(bar_vf + 8 * i, 1); mbar_init(bar_ve + 8 * i, 8);
        }
        fence_barrier_init();
    }
    __syncthreads();

    if (wg == 0) {
        reg_dealloc<40>();
        if (tid == 0) {
            for (int i = 0; i < 8; i++) {
                int b = i & 3;
                uint32_t buf = sK + b * A_TILE_BYTES;
                mbar_wait(bar_pe + 8 * b, ((i >> 2) & 1) ^ 1);
                mbar_expect_tx(bar_pf + 8 * b, A_TILE_BYTES);
                tma_load_2d(buf, &mapXn, bar_pf + 8 * b, i * 64, qt * 128);
                tma_load_2d(buf + 16384, &mapWq, bar_pf + 8 * b, head * DH, i * 64);
                tma_load_2d(buf + 16384 + 8192, &mapWq, bar_pf + 8 * b, head * DH + 64, i * 64);
            }
            for (int it = 0; it < NT; it++) {
                int s = it % A_KV_STAGES;
                uint32_t ph = (it / A_KV_STAGES) & 1;
                int row = head * SEQ + it * 128;
                if (it < A_KV_STAGES) mbar_wait(bar_pe + 8 * s, 1);
                else mbar_wait(bar_ke + 8 * s, ph ^ 1);
                mbar_expect_tx(bar_kf + 8 * s, A_TILE_BYTES);
                tma_load_2d(sK + s * A_TILE_BYTES, &mapK, bar_kf + 8 * s, 0, row);
                tma_load_2d(sK + s * A_TILE_BYTES + 16384, &mapK, bar_kf + 8 * s, 64, row);
                if (it < A_KV_STAGES) mbar_wait(bar_pe + 8 * (A_KV_STAGES + s), 1);
                else mbar_wait(bar_ve + 8 * s, ph ^ 1);
                mbar_expect_tx(bar_vf + 8 * s, A_TILE_BYTES);
                tma_load_2d(sV + s * A_TILE_BYTES, &mapV, bar_vf + 8 * s, 0, row);
                tma_load_2d(sV + s * A_TILE_BYTES + 16384, &mapV, bar_vf + 8 * s, 64, row);
            }
        }
    } else {
        reg_alloc<232>();
        int cw = wg - 1;
        int warp = tid >> 5, lane = tid & 31;
        float o[64];
        for (int i = 0; i < 8; i++) {
            int b = i & 3;
            uint32_t buf = sK + b * A_TILE_BYTES;
            mbar_wait(bar_pf + 8 * b, (i >> 2) & 1);
            wgmma_fence();
#pragma unroll
            for (int kk = 0; kk < 4; kk++)
                wgmma_m64n128k16_ss<0, 1>(o, make_desc(buf + cw * 8192 + kk * 32, 16, 1024),
                                          make_desc(buf + 16384 + kk * 2048, 8192, 1024), (i | kk) != 0);
            wgmma_commit();
            wgmma_wait<0>();
            if (lane == 0) mbar_arrive(bar_pe + 8 * b);
        }
        {
            int r = cw * 64 + warp * 16 + (lane >> 2);
#pragma unroll
            for (int j = 0; j < 16; j++) {
                uint32_t a = sQ + (j >> 3) * 16384 + r * 128 + (((j & 7) ^ (r & 7)) << 4) + (lane & 3) * 4;
                st_shared_u32(a, pack_bf16(o[j * 4 + 0], o[j * 4 + 1]));
                st_shared_u32(a + 1024, pack_bf16(o[j * 4 + 2], o[j * 4 + 3]));
            }
            fence_proxy_async();
            named_sync(3 + cw, 128);
        }
#pragma unroll
        for (int i = 0; i < 64; i++) o[i] = 0.f;
        float m0 = -INFINITY, m1 = -INFINITY, l0 = 0.f, l1 = 0.f;
        const float sc = 0.08838834764831845f * 1.4426950408889634f;
        if (cw == 1) named_arrive(1, 256);
        uint32_t qa = sQ + cw * 8192;
        float sacc[64];
        uint32_t p[32];
        mbar_wait(bar_kf, 0);
        named_sync(1 + cw, 256);
        wgmma_fence();
#pragma unroll
        for (int kk = 0; kk < 8; kk++) {
            uint32_t off = (kk >> 2) * 16384 + (kk & 3) * 32;
            wgmma_m64n128k16_ss<0, 0>(sacc, make_desc(qa + off, 16, 1024), make_desc(sK + off, 16, 1024), kk != 0);
        }
        wgmma_commit();
        named_arrive(1 + (cw ^ 1), 256);
        wgmma_wait<0>();
        if (lane == 0) mbar_arrive(bar_ke);
        {
            float mx0 = -INFINITY, mx1 = -INFINITY;
#pragma unroll
            for (int j = 0; j < 16; j++) {
                mx0 = fmaxf(mx0, fmaxf(sacc[j * 4 + 0], sacc[j * 4 + 1]));
                mx1 = fmaxf(mx1, fmaxf(sacc[j * 4 + 2], sacc[j * 4 + 3]));
            }
            mx0 = fmaxf(mx0, __shfl_xor_sync(0xffffffffu, mx0, 1));
            mx0 = fmaxf(mx0, __shfl_xor_sync(0xffffffffu, mx0, 2));
            mx1 = fmaxf(mx1, __shfl_xor_sync(0xffffffffu, mx1, 1));
            mx1 = fmaxf(mx1, __shfl_xor_sync(0xffffffffu, mx1, 2));
            m0 = mx0; m1 = mx1;
            float ms0 = mx0 * sc, ms1 = mx1 * sc;
#pragma unroll
            for (int j = 0; j < 16; j++) {
                float p0 = fast_exp2(sacc[j * 4 + 0] * sc - ms0);
                float p1 = fast_exp2(sacc[j * 4 + 1] * sc - ms0);
                float p2 = fast_exp2(sacc[j * 4 + 2] * sc - ms1);
                float p3 = fast_exp2(sacc[j * 4 + 3] * sc - ms1);
                l0 += p0 + p1; l1 += p2 + p3;
                p[j * 2 + 0] = pack_bf16(p0, p1);
                p[j * 2 + 1] = pack_bf16(p2, p3);
            }
        }
        for (int it = 1; it < NT; it++) {
            int s = it % A_KV_STAGES;
            uint32_t ph = (it / A_KV_STAGES) & 1;
            int sp = (it - 1) % A_KV_STAGES;
            uint32_t php = ((it - 1) / A_KV_STAGES) & 1;
            mbar_wait(bar_kf + 8 * s, ph);
            named_sync(1 + cw, 256);
            uint32_t kb = sK + s * A_TILE_BYTES;
            wgmma_fence();
#pragma unroll
            for (int kk = 0; kk < 8; kk++) {
                uint32_t off = (kk >> 2) * 16384 + (kk & 3) * 32;
                wgmma_m64n128k16_ss<0, 0>(sacc, make_desc(qa + off, 16, 1024), make_desc(kb + off, 16, 1024), kk != 0);
            }
            wgmma_commit();
            mbar_wait(bar_vf + 8 * sp, php);
            uint32_t vb = sV + sp * A_TILE_BYTES;
#pragma unroll
            for (int kk = 0; kk < 8; kk++) {
                wgmma_m64n128k16_rs<1>(o, p[kk * 4 + 0], p[kk * 4 + 1], p[kk * 4 + 2], p[kk * 4 + 3],
                                       make_desc(vb + kk * 2048, 16384, 1024), 1);
            }
            wgmma_commit();
            named_arrive(1 + (cw ^ 1), 256);
            wgmma_wait<1>();
            if (lane == 0) mbar_arrive(bar_ke + 8 * s);
            float mx0 = m0, mx1 = m1;
#pragma unroll
            for (int j = 0; j < 16; j++) {
                mx0 = fmaxf(mx0, fmaxf(sacc[j * 4 + 0], sacc[j * 4 + 1]));
                mx1 = fmaxf(mx1, fmaxf(sacc[j * 4 + 2], sacc[j * 4 + 3]));
            }
            mx0 = fmaxf(mx0, __shfl_xor_sync(0xffffffffu, mx0, 1));
            mx0 = fmaxf(mx0, __shfl_xor_sync(0xffffffffu, mx0, 2));
            mx1 = fmaxf(mx1, __shfl_xor_sync(0xffffffffu, mx1, 1));
            mx1 = fmaxf(mx1, __shfl_xor_sync(0xffffffffu, mx1, 2));
            float c0 = fast_exp2((m0 - mx0) * sc), c1 = fast_exp2((m1 - mx1) * sc);
            m0 = mx0; m1 = mx1;
            float ms0 = mx0 * sc, ms1 = mx1 * sc;
            float rs0 = 0.f, rs1 = 0.f;
#pragma unroll
            for (int j = 0; j < 16; j++) {
                sacc[j * 4 + 0] = fast_exp2(sacc[j * 4 + 0] * sc - ms0);
                sacc[j * 4 + 1] = fast_exp2(sacc[j * 4 + 1] * sc - ms0);
                sacc[j * 4 + 2] = fast_exp2(sacc[j * 4 + 2] * sc - ms1);
                sacc[j * 4 + 3] = fast_exp2(sacc[j * 4 + 3] * sc - ms1);
                rs0 += sacc[j * 4 + 0] + sacc[j * 4 + 1]; rs1 += sacc[j * 4 + 2] + sacc[j * 4 + 3];
            }
            l0 = l0 * c0 + rs0; l1 = l1 * c1 + rs1;
            wgmma_wait<0>();
            if (lane == 0) mbar_arrive(bar_ve + 8 * sp);
#pragma unroll
            for (int j = 0; j < 16; j++) {
                o[j * 4 + 0] *= c0; o[j * 4 + 1] *= c0; o[j * 4 + 2] *= c1; o[j * 4 + 3] *= c1;
                p[j * 2 + 0] = pack_bf16(sacc[j * 4 + 0], sacc[j * 4 + 1]);
                p[j * 2 + 1] = pack_bf16(sacc[j * 4 + 2], sacc[j * 4 + 3]);
            }
        }
        {
            int sp = (NT - 1) % A_KV_STAGES;
            uint32_t php = ((NT - 1) / A_KV_STAGES) & 1;
            mbar_wait(bar_vf + 8 * sp, php);
            uint32_t vb = sV + sp * A_TILE_BYTES;
            wgmma_fence();
#pragma unroll
            for (int kk = 0; kk < 8; kk++) {
                wgmma_m64n128k16_rs<1>(o, p[kk * 4 + 0], p[kk * 4 + 1], p[kk * 4 + 2], p[kk * 4 + 3],
                                       make_desc(vb + kk * 2048, 16384, 1024), 1);
            }
            wgmma_commit();
            wgmma_wait<0>();
        }
        l0 += __shfl_xor_sync(0xffffffffu, l0, 1);
        l0 += __shfl_xor_sync(0xffffffffu, l0, 2);
        l1 += __shfl_xor_sync(0xffffffffu, l1, 1);
        l1 += __shfl_xor_sync(0xffffffffu, l1, 2);
        float i0 = 1.f / l0, i1 = 1.f / l1;
        {
            int r = cw * 64 + warp * 16 + (lane >> 2);
#pragma unroll
            for (int j = 0; j < 16; j++) {
                uint32_t a = sQ + (j >> 3) * 16384 + r * 128 + (((j & 7) ^ (r & 7)) << 4) + (lane & 3) * 4;
                st_shared_u32(a, pack_bf16(o[j * 4 + 0] * i0, o[j * 4 + 1] * i0));
                st_shared_u32(a + 1024, pack_bf16(o[j * 4 + 2] * i1, o[j * 4 + 3] * i1));
            }
            named_sync(3 + cw, 128);
#pragma unroll
            for (int i = 0; i < 8; i++) {
                int idx = i * 128 + tid;
                int rr = cw * 64 + (idx >> 4), ch = idx & 15;
                uint32_t a = sQ + (ch >> 3) * 16384 + rr * 128 + (((ch & 7) ^ (rr & 7)) << 4);
                uint4 v = ld_shared_v4(a);
                *reinterpret_cast<uint4*>(g_o + (size_t)(qt * 128 + rr) * HD + head * DH + ch * 8) = v;
            }
        }
    }
}

constexpr int F_STAGES = 8;
constexpr int F_SMEM = F_STAGES * G_STAGE_BYTES + 1024 + 256;
__global__ void __launch_bounds__(256, 1)
final_kernel(const __grid_constant__ CUtensorMap mapO, const __grid_constant__ CUtensorMap mapWo,
             const __grid_constant__ CUtensorMap mapH, const __grid_constant__ CUtensorMap mapW2,
             const bf16* __restrict__ x, const bf16* __restrict__ b2, bf16* __restrict__ out) {
    extern __shared__ uint8_t smem_raw[];
    uint32_t sbase = (smem_u32(smem_raw) + 1023) & ~1023u;
    uint32_t bar_full = sbase + F_STAGES * G_STAGE_BYTES;
    uint32_t bar_empty = bar_full + 8 * F_STAGES;
    int wg = threadIdx.x >> 7;
    int tid = threadIdx.x & 127;
    int m0 = blockIdx.y * 64, n0 = blockIdx.x * 128;
    constexpr int NK1 = HD / 64;
    constexpr int NK2 = (FF + 63) / 64;

    if (threadIdx.x == 0) {
        for (int i = 0; i < F_STAGES; i++) { mbar_init(bar_full + 8 * i, 1); mbar_init(bar_empty + 8 * i, 4); }
        fence_barrier_init();
    }
    __syncthreads();

    if (wg == 0) {
        if (tid == 0) {
            for (int it = 0; it < NK1 + NK2; it++) {
                int s = it % F_STAGES;
                uint32_t ph = (it / F_STAGES) & 1;
                mbar_wait(bar_empty + 8 * s, ph ^ 1);
                mbar_expect_tx(bar_full + 8 * s, G_STAGE_BYTES);
                uint32_t a = sbase + s * G_STAGE_BYTES;
                const CUtensorMap* pa = it < NK2 ? &mapH : &mapO;
                const CUtensorMap* pb = it < NK2 ? &mapW2 : &mapWo;
                int k = (it < NK2 ? it : it - NK2) * 64;
                tma_load_2d(a, pa, bar_full + 8 * s, k, m0);
                tma_load_2d(a + 8192, pb, bar_full + 8 * s, n0, k);
                tma_load_2d(a + 8192 + 8192, pb, bar_full + 8 * s, n0 + 64, k);
            }
        }
    } else {
        float acc[64], acc2[64];
        int warp = tid >> 5, lane = tid & 31;
        int r = warp * 16 + (lane >> 2);
        uint32_t xv[32], bv[16];
#pragma unroll
        for (int j = 0; j < 16; j++) {
            int c = n0 + j * 8 + (lane & 3) * 2;
            bv[j] = *reinterpret_cast<const uint32_t*>(b2 + c);
            xv[j * 2] = *reinterpret_cast<const uint32_t*>(x + (size_t)(m0 + r) * DM + c);
            xv[j * 2 + 1] = *reinterpret_cast<const uint32_t*>(x + (size_t)(m0 + r + 8) * DM + c);
        }
        for (int it = 0; it < NK2; it++) {
            int s = it % F_STAGES;
            uint32_t ph = (it / F_STAGES) & 1;
            mbar_wait(bar_full + 8 * s, ph);
            uint32_t a = sbase + s * G_STAGE_BYTES;
            uint32_t b = a + 8192;
            wgmma_fence();
#pragma unroll
            for (int kk = 0; kk < 4; kk++)
                wgmma_m64n128k16_ss<0, 1>(acc2, make_desc(a + kk * 32, 16, 1024), make_desc(b + kk * 2048, 8192, 1024), (it | kk) != 0);
            wgmma_commit();
            wgmma_wait<1>();
            if (it > 0 && lane == 0) mbar_arrive(bar_empty + 8 * ((it - 1) % F_STAGES));
        }
        for (int it = NK2; it < NK1 + NK2; it++) {
            int s = it % F_STAGES;
            uint32_t ph = (it / F_STAGES) & 1;
            mbar_wait(bar_full + 8 * s, ph);
            uint32_t a = sbase + s * G_STAGE_BYTES;
            uint32_t b = a + 8192;
            wgmma_fence();
#pragma unroll
            for (int kk = 0; kk < 4; kk++)
                wgmma_m64n128k16_ss<0, 1>(acc, make_desc(a + kk * 32, 16, 1024), make_desc(b + kk * 2048, 8192, 1024), ((it - NK2) | kk) != 0);
            wgmma_commit();
            wgmma_wait<1>();
            if (lane == 0) mbar_arrive(bar_empty + 8 * ((it - 1) % F_STAGES));
        }
        wgmma_wait<0>();
#pragma unroll
        for (int j = 0; j < 16; j++) {
            float2 bf = __bfloat1622float2(*reinterpret_cast<const __nv_bfloat162*>(&bv[j]));
            uint32_t a = sbase + r * 256 + ((j ^ (r & 7)) << 4) + (lane & 3) * 4;
#pragma unroll
            for (int h = 0; h < 2; h++) {
                float2 xf = __bfloat1622float2(*reinterpret_cast<const __nv_bfloat162*>(&xv[j * 2 + h]));
                float g0 = acc2[j * 4 + h * 2 + 0] + bf.x, g1 = acc2[j * 4 + h * 2 + 1] + bf.y;
                g0 = __fdividef(g0, 1.f + __expf(-g0)); g1 = __fdividef(g1, 1.f + __expf(-g1));
                st_shared_u32(a + h * 2048, pack_bf16(xf.x + acc[j * 4 + h * 2 + 0] * g0, xf.y + acc[j * 4 + h * 2 + 1] * g1));
            }
        }
        named_sync(1, 128);
#pragma unroll
        for (int i = 0; i < 8; i++) {
            int idx = i * 128 + tid;
            int rr = idx >> 4, ch = idx & 15;
            uint4 v = ld_shared_v4(sbase + rr * 256 + ((ch ^ (rr & 7)) << 4));
            *reinterpret_cast<uint4*>(out + (size_t)(m0 + rr) * DM + n0 + ch * 8) = v;
        }
    }
}

typedef CUresult (*EncodeFn)(CUtensorMap*, CUtensorMapDataType, cuuint32_t, void*, const cuuint64_t*, const cuuint64_t*,
                             const cuuint32_t*, const cuuint32_t*, CUtensorMapInterleave, CUtensorMapSwizzle,
                             CUtensorMapL2promotion, CUtensorMapFloatOOBfill);

static void make_map(EncodeFn fn, CUtensorMap* m, const void* ptr, uint64_t inner, uint64_t outer,
                     uint32_t box_inner, uint32_t box_outer) {
    cuuint64_t dims[2] = {inner, outer};
    cuuint64_t strides[1] = {inner * 2};
    cuuint32_t box[2] = {box_inner, box_outer};
    cuuint32_t es[2] = {1, 1};
    fn(m, CU_TENSOR_MAP_DATA_TYPE_BFLOAT16, 2, const_cast<void*>(ptr), dims, strides, box, es,
       CU_TENSOR_MAP_INTERLEAVE_NONE, CU_TENSOR_MAP_SWIZZLE_128B, CU_TENSOR_MAP_L2_PROMOTION_L2_256B,
       CU_TENSOR_MAP_FLOAT_OOB_FILL_NONE);
}

extern "C" void kernel_launch(void* const* d_in, const int* in_sizes, int n_in, void* d_out, int out_size) {
    const bf16* x  = (const bf16*)d_in[0];
    const bf16* kc = (const bf16*)d_in[1];
    const bf16* vc = (const bf16*)d_in[2];
    const bf16* wq = (const bf16*)d_in[3];
    const bf16* wo = (const bf16*)d_in[4];
    const bf16* w1 = (const bf16*)d_in[6];
    const bf16* b1 = (const bf16*)d_in[7];
    const bf16* w2 = (const bf16*)d_in[8];
    const bf16* b2 = (const bf16*)d_in[9];
    bf16* out = (bf16*)d_out;

    static bool inited = false;
    static CUtensorMap mXn, mY, mWq, mW1, mQ, mK, mV, mO, mWo, mH, mW2;
    static void *pq, *ph;
    if (!inited) {
        EncodeFn fn = nullptr;
        cudaDriverEntryPointQueryResult qres;
        cudaGetDriverEntryPoint("cuTensorMapEncodeTiled", (void**)&fn, cudaEnableDefault, &qres);
        void *pxn, *py, *po;
        cudaGetSymbolAddress(&pxn, g_xn); cudaGetSymbolAddress(&py, g_y); cudaGetSymbolAddress(&pq, g_q);
        cudaGetSymbolAddress(&ph, g_h); cudaGetSymbolAddress(&po, g_o);
        make_map(fn, &mXn, pxn, DM, SEQ, 64, 128);
        make_map(fn, &mY, py, DM, SEQ, 64, 64);
        make_map(fn, &mWq, wq, HD, DM, 64, 64);
        make_map(fn, &mW1, w1, FF, DM, 64, 64);
        make_map(fn, &mK, kc, DH, NH * SEQ, 64, 128);
        make_map(fn, &mV, vc, DH, NH * SEQ, 64, 128);
        make_map(fn, &mO, po, HD, SEQ, 64, 64);
        make_map(fn, &mWo, wo, DM, HD, 64, 64);
        make_map(fn, &mH, ph, FF, SEQ, 64, 64);
        make_map(fn, &mW2, w2, DM, FF, 64, 64);
        cudaFuncSetAttribute(mlp1_kernel, cudaFuncAttributeMaxDynamicSharedMemorySize, M1_SMEM);
        cudaFuncSetAttribute(final_kernel, cudaFuncAttributeMaxDynamicSharedMemorySize, F_SMEM);
        cudaFuncSetAttribute(attn_kernel, cudaFuncAttributeMaxDynamicSharedMemorySize, A_SMEM);
        inited = true;
    }

    ln_kernel<<<SEQ / 8, 256>>>(x);
    mlp1_kernel<<<dim3((FF + 127) / 128, SEQ / 64), 256, M1_SMEM>>>(mY, mW1, (bf16*)ph, b1);
    attn_kernel<<<dim3(SEQ / 128, NH), 384, A_SMEM>>>(mXn, mWq, mK, mV);
    final_kernel<<<dim3(DM / 128, SEQ / 64), 256, F_SMEM>>>(mO, mWo, mH, mW2, x, b2, out);
}
```

```cpp
#include <cuda_runtime.h>
#include <cuda_bf16.h>
#include <cuda.h>
#include <stdint.h>

typedef __nv_bfloat16 bf16;

constexpr int SEQ = 2048;
constexpr int DM  = 512;
constexpr int NH  = 32;
constexpr int DH  = 128;
constexpr int HD  = NH * DH;
constexpr int FF  = 1376;

__device__ bf16 g_xn[SEQ * DM];
__device__ bf16 g_y [SEQ * DM];
__device__ bf16 g_q [SEQ * HD];
__device__ bf16 g_h [SEQ * FF];
__device__ bf16 g_o [SEQ * HD];

__device__ __forceinline__ uint32_t smem_u32(const void* p) {
    return (uint32_t)__cvta_generic_to_shared(p);
}
__device__ __forceinline__ void mbar_init(uint32_t bar, uint32_t count) {
    asm volatile("mbarrier.init.shared::cta.b64 [%0], %1;" :: "r"(bar), "r"(count) : "memory");
}
__device__ __forceinline__ void mbar_arrive(uint32_t bar) {
    asm volatile("mbarrier.arrive.shared::cta.b64 _, [%0];" :: "r"(bar) : "memory");
}
__device__ __forceinline__ void mbar_expect_tx(uint32_t bar, uint32_t bytes) {
    asm volatile("mbarrier.arrive.expect_tx.shared::cta.b64 _, [%0], %1;" :: "r"(bar), "r"(bytes) : "memory");
}
__device__ __forceinline__ void mbar_wait(uint32_t bar, uint32_t parity) {
    asm volatile(
        "{\n"
        ".reg .pred p;\n"
        "LAB_WAIT:\n"
        "mbarrier.try_wait.parity.shared::cta.b64 p, [%0], %1;\n"
        "@p bra DONE;\n"
        "bra LAB_WAIT;\n"
        "DONE:\n"
        "}\n" :: "r"(bar), "r"(parity) : "memory");
}
__device__ __forceinline__ void tma_load_2d(uint32_t dst, const CUtensorMap* map, uint32_t bar, int c0, int c1) {
    asm volatile(
        "cp.async.bulk.tensor.2d.shared::cluster.global.mbarrier::complete_tx::bytes [%0], [%1, {%3, %4}], [%2];"
        :: "r"(dst), "l"((uint64_t)map), "r"(bar), "r"(c0), "r"(c1) : "memory");
}
__device__ __forceinline__ void wgmma_fence() { asm volatile("wgmma.fence.sync.aligned;" ::: "memory"); }
__device__ __forceinline__ void wgmma_commit() { asm volatile("wgmma.commit_group.sync.aligned;" ::: "memory"); }
template <int N> __device__ __forceinline__ void wgmma_wait() {
    asm volatile("wgmma.wait_group.sync.aligned %0;" :: "n"(N) : "memory");
}
template <int R> __device__ __forceinline__ void reg_alloc() {
    asm volatile("setmaxnreg.inc.sync.aligned.u32 %0;" :: "n"(R));
}
template <int R> __device__ __forceinline__ void reg_dealloc() {
    asm volatile("setmaxnreg.dec.sync.aligned.u32 %0;" :: "n"(R));
}
__device__ __forceinline__ void fence_barrier_init() {
    asm volatile("fence.mbarrier_init.release.cluster;" ::: "memory");
}
__device__ __forceinline__ void fence_proxy_async() {
    asm volatile("fence.proxy.async.shared::cta;" ::: "memory");
}

__device__ __forceinline__ void named_sync(int id, int n) {
    asm volatile("bar.sync %0, %1;" :: "r"(id), "r"(n) : "memory");
}
__device__ __forceinline__ void named_arrive(int id, int n) {
    asm volatile("bar.arrive %0, %1;" :: "r"(id), "r"(n) : "memory");
}
__device__ __forceinline__ float fast_exp2(float x) {
    float y;
    asm("ex2.approx.ftz.f32 %0, %1;" : "=f"(y) : "f"(x));
    return y;
}

__device__ __forceinline__ void st_shared_u32(uint32_t a, uint32_t v) {
    asm volatile("st.shared.u32 [%0], %1;" :: "r"(a), "r"(v) : "memory");
}
__device__ __forceinline__ uint4 ld_shared_v4(uint32_t a) {
    uint4 v;
    asm volatile("ld.shared.v4.u32 {%0,%1,%2,%3}, [%4];" : "=r"(v.x), "=r"(v.y), "=r"(v.z), "=r"(v.w) : "r"(a) : "memory");
    return v;
}

__device__ __forceinline__ uint64_t make_desc(uint32_t addr, uint32_t lbo_bytes, uint32_t sbo_bytes) {
    uint64_t d = 0;
    d |= (uint64_t)((addr & 0x3FFFF) >> 4);
    d |= (uint64_t)((lbo_bytes & 0x3FFFF) >> 4) << 16;
    d |= (uint64_t)((sbo_bytes & 0x3FFFF) >> 4) << 32;
    d |= (uint64_t)1 << 62;
    return d;
}

template <int TA, int TB>
__device__ __forceinline__ void wgmma_m64n128k16_ss(float (&d)[64], uint64_t da, uint64_t db, int scale_d) {
    asm volatile(
        "{\n.reg .pred p;\nsetp.ne.b32 p, %66, 0;\n"
        "wgmma.mma_async.sync.aligned.m64n128k16.f32.bf16.bf16 "
        "{%0,%1,%2,%3,%4,%5,%6,%7,%8,%9,%10,%11,%12,%13,%14,%15,"
        "%16,%17,%18,%19,%20,%21,%22,%23,%24,%25,%26,%27,%28,%29,%30,%31,"
        "%32,%33,%34,%35,%36,%37,%38,%39,%40,%41,%42,%43,%44,%45,%46,%47,"
        "%48,%49,%50,%51,%52,%53,%54,%55,%56,%57,%58,%59,%60,%61,%62,%63},"
        " %64, %65, p, 1, 1, %67, %68;\n}\n"
        : "+f"(d[0]), "+f"(d[1]), "+f"(d[2]), "+f"(d[3]), "+f"(d[4]), "+f"(d[5]), "+f"(d[6]), "+f"(d[7]),
          "+f"(d[8]), "+f"(d[9]), "+f"(d[10]), "+f"(d[11]), "+f"(d[12]), "+f"(d[13]), "+f"(d[14]), "+f"(d[15]),
          "+f"(d[16]), "+f"(d[17]), "+f"(d[18]), "+f"(d[19]), "+f"(d[20]), "+f"(d[21]), "+f"(d[22]), "+f"(d[23]),
          "+f"(d[24]), "+f"(d[25]), "+f"(d[26]), "+f"(d[27]), "+f"(d[28]), "+f"(d[29]), "+f"(d[30]), "+f"(d[31]),
          "+f"(d[32]), "+f"(d[33]), "+f"(d[34]), "+f"(d[35]), "+f"(d[36]), "+f"(d[37]), "+f"(d[38]), "+f"(d[39]),
          "+f"(d[40]), "+f"(d[41]), "+f"(d[42]), "+f"(d[43]), "+f"(d[44]), "+f"(d[45]), "+f"(d[46]), "+f"(d[47]),
          "+f"(d[48]), "+f"(d[49]), "+f"(d[50]), "+f"(d[51]), "+f"(d[52]), "+f"(d[53]), "+f"(d[54]), "+f"(d[55]),
          "+f"(d[56]), "+f"(d[57]), "+f"(d[58]), "+f"(d[59]), "+f"(d[60]), "+f"(d[61]), "+f"(d[62]), "+f"(d[63])
        : "l"(da), "l"(db), "r"(scale_d), "n"(TA), "n"(TB));
}

template <int TB>
__device__ __forceinline__ void wgmma_m64n128k16_rs(float (&d)[64], uint32_t a0, uint32_t a1, uint32_t a2, uint32_t a3,
                                                    uint64_t db, int scale_d) {
    asm volatile(
        "{\n.reg .pred p;\nsetp.ne.b32 p, %69, 0;\n"
        "wgmma.mma_async.sync.aligned.m64n128k16.f32.bf16.bf16 "
        "{%0,%1,%2,%3,%4,%5,%6,%7,%8,%9,%10,%11,%12,%13,%14,%15,"
        "%16,%17,%18,%19,%20,%21,%22,%23,%24,%25,%26,%27,%28,%29,%30,%31,"
        "%32,%33,%34,%35,%36,%37,%38,%39,%40,%41,%42,%43,%44,%45,%46,%47,"
        "%48,%49,%50,%51,%52,%53,%54,%55,%56,%57,%58,%59,%60,%61,%62,%63},"
        " {%64,%65,%66,%67}, %68, p, 1, 1, %70;\n}\n"
        : "+f"(d[0]), "+f"(d[1]), "+f"(d[2]), "+f"(d[3]), "+f"(d[4]), "+f"(d[5]), "+f"(d[6]), "+f"(d[7]),
          "+f"(d[8]), "+f"(d[9]), "+f"(d[10]), "+f"(d[11]), "+f"(d[12]), "+f"(d[13]), "+f"(d[14]), "+f"(d[15]),
          "+f"(d[16]), "+f"(d[17]), "+f"(d[18]), "+f"(d[19]), "+f"(d[20]), "+f"(d[21]), "+f"(d[22]), "+f"(d[23]),
          "+f"(d[24]), "+f"(d[25]), "+f"(d[26]), "+f"(d[27]), "+f"(d[28]), "+f"(d[29]), "+f"(d[30]), "+f"(d[31]),
          "+f"(d[32]), "+f"(d[33]), "+f"(d[34]), "+f"(d[35]), "+f"(d[36]), "+f"(d[37]), "+f"(d[38]), "+f"(d[39]),
          "+f"(d[40]), "+f"(d[41]), "+f"(d[42]), "+f"(d[43]), "+f"(d[44]), "+f"(d[45]), "+f"(d[46]), "+f"(d[47]),
          "+f"(d[48]), "+f"(d[49]), "+f"(d[50]), "+f"(d[51]), "+f"(d[52]), "+f"(d[53]), "+f"(d[54]), "+f"(d[55]),
          "+f"(d[56]), "+f"(d[57]), "+f"(d[58]), "+f"(d[59]), "+f"(d[60]), "+f"(d[61]), "+f"(d[62]), "+f"(d[63])
        : "r"(a0), "r"(a1), "r"(a2), "r"(a3), "l"(db), "r"(scale_d), "n"(TB));
}

__device__ __forceinline__ uint32_t pack_bf16(float lo, float hi) {
    __nv_bfloat162 v = __floats2bfloat162_rn(lo, hi);
    return *reinterpret_cast<uint32_t*>(&v);
}

__global__ void __launch_bounds__(256) ln_kernel(const bf16* __restrict__ x) {
    int warp = threadIdx.x >> 5, lane = threadIdx.x & 31;
    int row = blockIdx.x * 8 + warp;
    const uint4* src = reinterpret_cast<const uint4*>(x + (size_t)row * DM);
    float v[16];
#pragma unroll
    for (int i = 0; i < 2; i++) {
        uint4 u = src[lane + i * 32];
        const __nv_bfloat162* h = reinterpret_cast<const __nv_bfloat162*>(&u);
#pragma unroll
        for (int j = 0; j < 4; j++) {
            float2 f = __bfloat1622float2(h[j]);
            v[i * 8 + j * 2] = f.x; v[i * 8 + j * 2 + 1] = f.y;
        }
    }
#pragma unroll
    for (int pass = 0; pass < 2; pass++) {
        float s = 0.f;
#pragma unroll
        for (int i = 0; i < 16; i++) s += v[i];
#pragma unroll
        for (int o = 16; o > 0; o >>= 1) s += __shfl_xor_sync(0xffffffffu, s, o);
        float mean = s * (1.f / DM);
        float q = 0.f;
#pragma unroll
        for (int i = 0; i < 16; i++) { float d = v[i] - mean; q += d * d; }
#pragma unroll
        for (int o = 16; o > 0; o >>= 1) q += __shfl_xor_sync(0xffffffffu, q, o);
        float rstd = 1.0f / sqrtf(q * (1.f / DM) + 1e-5f);
        bf16* dst = (pass == 0 ? g_xn : g_y) + (size_t)row * DM;
#pragma unroll
        for (int i = 0; i < 2; i++) {
            uint4 u;
            uint32_t* w = reinterpret_cast<uint32_t*>(&u);
#pragma unroll
            for (int j = 0; j < 4; j++) {
                __nv_bfloat162 h = __floats2bfloat162_rn((v[i * 8 + j * 2] - mean) * rstd, (v[i * 8 + j * 2 + 1] - mean) * rstd);
                w[j] = *reinterpret_cast<uint32_t*>(&h);
                float2 f = __bfloat1622float2(h);
                v[i * 8 + j * 2] = f.x; v[i * 8 + j * 2 + 1] = f.y;
            }
            reinterpret_cast<uint4*>(dst)[lane + i * 32] = u;
        }
    }
}

constexpr int G_STAGE_BYTES = 8192 + 16384;

__device__ __forceinline__ float gelu_tanh(float x) {
    float u = 0.7978845608028654f * (x + 0.044715f * x * x * x);
    float t = 1.f - __fdividef(2.f, 1.f + __expf(2.f * u));
    return 0.5f * x * (1.f + t);
}

constexpr int M1_STAGES = 4;
constexpr int M1_SMEM = M1_STAGES * G_STAGE_BYTES + 1024 + 256;
__global__ void __launch_bounds__(256, 2)
mlp1_kernel(const __grid_constant__ CUtensorMap mapA, const __grid_constant__ CUtensorMap mapB,
            bf16* __restrict__ C, const bf16* __restrict__ bias) {
    extern __shared__ uint8_t smem_raw[];
    uint32_t sbase = (smem_u32(smem_raw) + 1023) & ~1023u;
    uint32_t bar_full = sbase + M1_STAGES * G_STAGE_BYTES;
    uint32_t bar_empty = bar_full + 8 * M1_STAGES;
    int wg = threadIdx.x >> 7;
    int tid = threadIdx.x & 127;
    int m0 = blockIdx.y * 64, n0 = blockIdx.x * 128;
    constexpr int nk = DM / 64;

    if (threadIdx.x == 0) {
        for (int i = 0; i < M1_STAGES; i++) { mbar_init(bar_full + 8 * i, 1); mbar_init(bar_empty + 8 * i, 4); }
        fence_barrier_init();
    }
    __syncthreads();

    if (wg == 0) {
        if (tid == 0) {
            for (int it = 0; it < nk; it++) {
                int s = it % M1_STAGES;
                uint32_t ph = (it / M1_STAGES) & 1;
                mbar_wait(bar_empty + 8 * s, ph ^ 1);
                mbar_expect_tx(bar_full + 8 * s, G_STAGE_BYTES);
                uint32_t a = sbase + s * G_STAGE_BYTES;
                tma_load_2d(a, &mapA, bar_full + 8 * s, it * 64, m0);
                tma_load_2d(a + 8192, &mapB, bar_full + 8 * s, n0, it * 64);
                tma_load_2d(a + 8192 + 8192, &mapB, bar_full + 8 * s, n0 + 64, it * 64);
            }
        }
    } else {
        float acc[64];
        int warp = tid >> 5, lane = tid & 31;
        uint32_t bv[16];
#pragma unroll
        for (int j = 0; j < 16; j++) {
            int c = min(n0 + j * 8 + (lane & 3) * 2, FF - 2);
            bv[j] = *reinterpret_cast<const uint32_t*>(bias + c);
        }
        for (int it = 0; it < nk; it++) {
            int s = it % M1_STAGES;
            uint32_t ph = (it / M1_STAGES) & 1;
            mbar_wait(bar_full + 8 * s, ph);
            uint32_t a = sbase + s * G_STAGE_BYTES;
            uint32_t b = a + 8192;
            wgmma_fence();
#pragma unroll
            for (int kk = 0; kk < 4; kk++)
                wgmma_m64n128k16_ss<0, 1>(acc, make_desc(a + kk * 32, 16, 1024), make_desc(b + kk * 2048, 8192, 1024), (it | kk) != 0);
            wgmma_commit();
            wgmma_wait<1>();
            if (it > 0 && lane == 0) mbar_arrive(bar_empty + 8 * ((it - 1) % M1_STAGES));
        }
        wgmma_wait<0>();
        int r = warp * 16 + (lane >> 2);
#pragma unroll
        for (int j = 0; j < 16; j++) {
            float2 bf = __bfloat1622float2(*reinterpret_cast<const __nv_bfloat162*>(&bv[j]));
            float b0 = bf.x, b1 = bf.y;
            uint32_t a = sbase + r * 256 + ((j ^ (r & 7)) << 4) + (lane & 3) * 4;
            st_shared_u32(a, pack_bf16(gelu_tanh(acc[j * 4 + 0] + b0), gelu_tanh(acc[j * 4 + 1] + b1)));
            st_shared_u32(a + 2048, pack_bf16(gelu_tanh(acc[j * 4 + 2] + b0), gelu_tanh(acc[j * 4 + 3] + b1)));
        }
        named_sync(1, 128);
#pragma unroll
        for (int i = 0; i < 8; i++) {
            int idx = i * 128 + tid;
            int rr = idx >> 4, ch = idx & 15;
            uint4 v = ld_shared_v4(sbase + rr * 256 + ((ch ^ (rr & 7)) << 4));
            if (n0 + ch * 8 < FF)
                *reinterpret_cast<uint4*>(C + (size_t)(m0 + rr) * FF + n0 + ch * 8) = v;
        }
    }
}

constexpr int A_KV_STAGES = 2;
constexpr int A_TILE_BYTES = 128 * 128 * 2;
constexpr int A_SMEM = A_TILE_BYTES * (1 + 2 * A_KV_STAGES) + 1024 + 256;

__global__ void __launch_bounds__(384, 1)
attn_kernel(const __grid_constant__ CUtensorMap mapXn, const __grid_constant__ CUtensorMap mapWq,
            const __grid_constant__ CUtensorMap mapK, const __grid_constant__ CUtensorMap mapV) {
    extern __shared__ uint8_t smem_raw[];
    uint32_t sbase = (smem_u32(smem_raw) + 1023) & ~1023u;
    uint32_t sQ = sbase;
    uint32_t sK = sQ + A_TILE_BYTES;
    uint32_t sV = sK + A_KV_STAGES * A_TILE_BYTES;
    uint32_t bars = sV + A_KV_STAGES * A_TILE_BYTES;
    uint32_t bar_pf = bars, bar_pe = bars + 32;
    uint32_t bar_kf = bars + 64, bar_ke = bar_kf + 8 * A_KV_STAGES;
    uint32_t bar_vf = bar_ke + 8 * A_KV_STAGES, bar_ve = bar_vf + 8 * A_KV_STAGES;
    int wg = threadIdx.x >> 7;
    int tid = threadIdx.x & 127;
    int qt = blockIdx.x, head = blockIdx.y;
    constexpr int NT = SEQ / 128;

    if (threadIdx.x == 0) {
        for (int i = 0; i < 4; i++) { mbar_init(bar_pf + 8 * i, 1); mbar_init(bar_pe + 8 * i, 8); }
        for (int i = 0; i < A_KV_STAGES; i++) {
            mbar_init(bar_kf + 8 * i, 1); mbar_init(bar_ke + 8 * i, 8);
            mbar_init(bar_vf + 8 * i, 1); mbar_init(bar_ve + 8 * i, 8);
        }
        fence_barrier_init();
    }
    __syncthreads();

    if (wg == 0) {
        reg_dealloc<40>();
        if (tid == 0) {
            for (int i = 0; i < 8; i++) {
                int b = i & 3;
                uint32_t buf = sK + b * A_TILE_BYTES;
                mbar_wait(bar_pe + 8 * b, ((i >> 2) & 1) ^ 1);
                mbar_expect_tx(bar_pf + 8 * b, A_TILE_BYTES);
                tma_load_2d(buf, &mapXn, bar_pf + 8 * b, i * 64, qt * 128);
                tma_load_2d(buf + 16384, &mapWq, bar_pf + 8 * b, head * DH, i * 64);
                tma_load_2d(buf + 16384 + 8192, &mapWq, bar_pf + 8 * b, head * DH + 64, i * 64);
            }
            for (int it = 0; it < NT; it++) {
                int s = it % A_KV_STAGES;
                uint32_t ph = (it / A_KV_STAGES) & 1;
                int row = head * SEQ + it * 128;
                if (it < A_KV_STAGES) mbar_wait(bar_pe + 8 * s, 1);
                else mbar_wait(bar_ke + 8 * s, ph ^ 1);
                mbar_expect_tx(bar_kf + 8 * s, A_TILE_BYTES);
                tma_load_2d(sK + s * A_TILE_BYTES, &mapK, bar_kf + 8 * s, 0, row);
                tma_load_2d(sK + s * A_TILE_BYTES + 16384, &mapK, bar_kf + 8 * s, 64, row);
                if (it < A_KV_STAGES) mbar_wait(bar_pe + 8 * (A_KV_STAGES + s), 1);
                else mbar_wait(bar_ve + 8 * s, ph ^ 1);
                mbar_expect_tx(bar_vf + 8 * s, A_TILE_BYTES);
                tma_load_2d(sV + s * A_TILE_BYTES, &mapV, bar_vf + 8 * s, 0, row);
                tma_load_2d(sV + s * A_TILE_BYTES + 16384, &mapV, bar_vf + 8 * s, 64, row);
            }
        }
    } else {
        reg_alloc<232>();
        int cw = wg - 1;
        int warp = tid >> 5, lane = tid & 31;
        float o[64];
        for (int i = 0; i < 8; i++) {
            int b = i & 3;
            uint32_t buf = sK + b * A_TILE_BYTES;
            mbar_wait(bar_pf + 8 * b, (i >> 2) & 1);
            wgmma_fence();
#pragma unroll
            for (int kk = 0; kk < 4; kk++)
                wgmma_m64n128k16_ss<0, 1>(o, make_desc(buf + cw * 8192 + kk * 32, 16, 1024),
                                          make_desc(buf + 16384 + kk * 2048, 8192, 1024), (i | kk) != 0);
            wgmma_commit();
            wgmma_wait<0>();
            if (lane == 0) mbar_arrive(bar_pe + 8 * b);
        }
        {
            int r = cw * 64 + warp * 16 + (lane >> 2);
#pragma unroll
            for (int j = 0; j < 16; j++) {
                uint32_t a = sQ + (j >> 3) * 16384 + r * 128 + (((j & 7) ^ (r & 7)) << 4) + (lane & 3) * 4;
                st_shared_u32(a, pack_bf16(o[j * 4 + 0], o[j * 4 + 1]));
                st_shared_u32(a + 1024, pack_bf16(o[j * 4 + 2], o[j * 4 + 3]));
            }
            fence_proxy_async();
            named_sync(3 + cw, 128);
        }
#pragma unroll
        for (int i = 0; i < 64; i++) o[i] = 0.f;
        float m0 = -INFINITY, m1 = -INFINITY, l0 = 0.f, l1 = 0.f;
        const float sc = 0.08838834764831845f * 1.4426950408889634f;
        if (cw == 1) named_arrive(1, 256);
        uint32_t qa = sQ + cw * 8192;
        float sacc[64];
        uint32_t p[32];
        mbar_wait(bar_kf, 0);
        named_sync(1 + cw, 256);
        wgmma_fence();
#pragma unroll
        for (int kk = 0; kk < 8; kk++) {
            uint32_t off = (kk >> 2) * 16384 + (kk & 3) * 32;
            wgmma_m64n128k16_ss<0, 0>(sacc, make_desc(qa + off, 16, 1024), make_desc(sK + off, 16, 1024), kk != 0);
        }
        wgmma_commit();
        named_arrive(1 + (cw ^ 1), 256);
        wgmma_wait<0>();
        if (lane == 0) mbar_arrive(bar_ke);
        {
            float mx0 = -INFINITY, mx1 = -INFINITY;
#pragma unroll
            for (int j = 0; j < 16; j++) {
                mx0 = fmaxf(mx0, fmaxf(sacc[j * 4 + 0], sacc[j * 4 + 1]));
                mx1 = fmaxf(mx1, fmaxf(sacc[j * 4 + 2], sacc[j * 4 + 3]));
            }
            mx0 = fmaxf(mx0, __shfl_xor_sync(0xffffffffu, mx0, 1));
            mx0 = fmaxf(mx0, __shfl_xor_sync(0xffffffffu, mx0, 2));
            mx1 = fmaxf(mx1, __shfl_xor_sync(0xffffffffu, mx1, 1));
            mx1 = fmaxf(mx1, __shfl_xor_sync(0xffffffffu, mx1, 2));
            m0 = mx0; m1 = mx1;
            float ms0 = mx0 * sc, ms1 = mx1 * sc;
#pragma unroll
            for (int j = 0; j < 16; j++) {
                float p0 = fast_exp2(sacc[j * 4 + 0] * sc - ms0);
                float p1 = fast_exp2(sacc[j * 4 + 1] * sc - ms0);
                float p2 = fast_exp2(sacc[j * 4 + 2] * sc - ms1);
                float p3 = fast_exp2(sacc[j * 4 + 3] * sc - ms1);
                l0 += p0 + p1; l1 += p2 + p3;
                p[j * 2 + 0] = pack_bf16(p0, p1);
                p[j * 2 + 1] = pack_bf16(p2, p3);
            }
        }
        for (int it = 1; it < NT; it++) {
            int s = it % A_KV_STAGES;
            uint32_t ph = (it / A_KV_STAGES) & 1;
            int sp = (it - 1) % A_KV_STAGES;
            uint32_t php = ((it - 1) / A_KV_STAGES) & 1;
            mbar_wait(bar_kf + 8 * s, ph);
            named_sync(1 + cw, 256);
            uint32_t kb = sK + s * A_TILE_BYTES;
            wgmma_fence();
#pragma unroll
            for (int kk = 0; kk < 8; kk++) {
                uint32_t off = (kk >> 2) * 16384 + (kk & 3) * 32;
                wgmma_m64n128k16_ss<0, 0>(sacc, make_desc(qa + off, 16, 1024), make_desc(kb + off, 16, 1024), kk != 0);
            }
            wgmma_commit();
            mbar_wait(bar_vf + 8 * sp, php);
            uint32_t vb = sV + sp * A_TILE_BYTES;
#pragma unroll
            for (int kk = 0; kk < 8; kk++) {
                wgmma_m64n128k16_rs<1>(o, p[kk * 4 + 0], p[kk * 4 + 1], p[kk * 4 + 2], p[kk * 4 + 3],
                                       make_desc(vb + kk * 2048, 16384, 1024), 1);
            }
            wgmma_commit();
            named_arrive(1 + (cw ^ 1), 256);
            wgmma_wait<1>();
            if (lane == 0) mbar_arrive(bar_ke + 8 * s);
            float mx0 = m0, mx1 = m1;
#pragma unroll
            for (int j = 0; j < 16; j++) {
                mx0 = fmaxf(mx0, fmaxf(sacc[j * 4 + 0], sacc[j * 4 + 1]));
                mx1 = fmaxf(mx1, fmaxf(sacc[j * 4 + 2], sacc[j * 4 + 3]));
            }
            mx0 = fmaxf(mx0, __shfl_xor_sync(0xffffffffu, mx0, 1));
            mx0 = fmaxf(mx0, __shfl_xor_sync(0xffffffffu, mx0, 2));
            mx1 = fmaxf(mx1, __shfl_xor_sync(0xffffffffu, mx1, 1));
            mx1 = fmaxf(mx1, __shfl_xor_sync(0xffffffffu, mx1, 2));
            float c0 = fast_exp2((m0 - mx0) * sc), c1 = fast_exp2((m1 - mx1) * sc);
            m0 = mx0; m1 = mx1;
            float ms0 = mx0 * sc, ms1 = mx1 * sc;
            float rs0 = 0.f, rs1 = 0.f;
#pragma unroll
            for (int j = 0; j < 16; j++) {
                sacc[j * 4 + 0] = fast_exp2(sacc[j * 4 + 0] * sc - ms0);
                sacc[j * 4 + 1] = fast_exp2(sacc[j * 4 + 1] * sc - ms0);
                sacc[j * 4 + 2] = fast_exp2(sacc[j * 4 + 2] * sc - ms1);
                sacc[j * 4 + 3] = fast_exp2(sacc[j * 4 + 3] * sc - ms1);
                rs0 += sacc[j * 4 + 0] + sacc[j * 4 + 1]; rs1 += sacc[j * 4 + 2] + sacc[j * 4 + 3];
            }
            l0 = l0 * c0 + rs0; l1 = l1 * c1 + rs1;
            wgmma_wait<0>();
            if (lane == 0) mbar_arrive(bar_ve + 8 * sp);
#pragma unroll
            for (int j = 0; j < 16; j++) {
                o[j * 4 + 0] *= c0; o[j * 4 + 1] *= c0; o[j * 4 + 2] *= c1; o[j * 4 + 3] *= c1;
                p[j * 2 + 0] = pack_bf16(sacc[j * 4 + 0], sacc[j * 4 + 1]);
                p[j * 2 + 1] = pack_bf16(sacc[j * 4 + 2], sacc[j * 4 + 3]);
            }
        }
        {
            int sp = (NT - 1) % A_KV_STAGES;
            uint32_t php = ((NT - 1) / A_KV_STAGES) & 1;
            mbar_wait(bar_vf + 8 * sp, php);
            uint32_t vb = sV + sp * A_TILE_BYTES;
            wgmma_fence();
#pragma unroll
            for (int kk = 0; kk < 8; kk++) {
                wgmma_m64n128k16_rs<1>(o, p[kk * 4 + 0], p[kk * 4 + 1], p[kk * 4 + 2], p[kk * 4 + 3],
                                       make_desc(vb + kk * 2048, 16384, 1024), 1);
            }
            wgmma_commit();
            wgmma_wait<0>();
        }
        l0 += __shfl_xor_sync(0xffffffffu, l0, 1);
        l0 += __shfl_xor_sync(0xffffffffu, l0, 2);
        l1 += __shfl_xor_sync(0xffffffffu, l1, 1);
        l1 += __shfl_xor_sync(0xffffffffu, l1, 2);
        float i0 = 1.f / l0, i1 = 1.f / l1;
        {
            int r = cw * 64 + warp * 16 + (lane >> 2);
#pragma unroll
            for (int j = 0; j < 16; j++) {
                uint32_t a = sQ + (j >> 3) * 16384 + r * 128 + (((j & 7) ^ (r & 7)) << 4) + (lane & 3) * 4;
                st_shared_u32(a, pack_bf16(o[j * 4 + 0] * i0, o[j * 4 + 1] * i0));
                st_shared_u32(a + 1024, pack_bf16(o[j * 4 + 2] * i1, o[j * 4 + 3] * i1));
            }
            named_sync(3 + cw, 128);
#pragma unroll
            for (int i = 0; i < 8; i++) {
                int idx = i * 128 + tid;
                int rr = cw * 64 + (idx >> 4), ch = idx & 15;
                uint32_t a = sQ + (ch >> 3) * 16384 + rr * 128 + (((ch & 7) ^ (rr & 7)) << 4);
                uint4 v = ld_shared_v4(a);
                *reinterpret_cast<uint4*>(g_o + (size_t)(qt * 128 + rr) * HD + head * DH + ch * 8) = v;
            }
        }
    }
}

constexpr int F_STAGES = 8;
constexpr int F_SMEM = F_STAGES * G_STAGE_BYTES + 1024 + 256;
__global__ void __launch_bounds__(256, 1)
final_kernel(const __grid_constant__ CUtensorMap mapO, const __grid_constant__ CUtensorMap mapWo,
             const __grid_constant__ CUtensorMap mapH, const __grid_constant__ CUtensorMap mapW2,
             const bf16* __restrict__ x, const bf16* __restrict__ b2, bf16* __restrict__ out) {
    extern __shared__ uint8_t smem_raw[];
    uint32_t sbase = (smem_u32(smem_raw) + 1023) & ~1023u;
    uint32_t bar_full = sbase + F_STAGES * G_STAGE_BYTES;
    uint32_t bar_empty = bar_full + 8 * F_STAGES;
    int wg = threadIdx.x >> 7;
    int tid = threadIdx.x & 127;
    int m0 = blockIdx.y * 64, n0 = blockIdx.x * 128;
    constexpr int NK1 = HD / 64;
    constexpr int NK2 = (FF + 63) / 64;

    if (threadIdx.x == 0) {
        for (int i = 0; i < F_STAGES; i++) { mbar_init(bar_full + 8 * i, 1); mbar_init(bar_empty + 8 * i, 4); }
        fence_barrier_init();
    }
    __syncthreads();

    if (wg == 0) {
        if (tid == 0) {
            for (int it = 0; it < NK1 + NK2; it++) {
                int s = it % F_STAGES;
                uint32_t ph = (it / F_STAGES) & 1;
                mbar_wait(bar_empty + 8 * s, ph ^ 1);
                mbar_expect_tx(bar_full + 8 * s, G_STAGE_BYTES);
                uint32_t a = sbase + s * G_STAGE_BYTES;
                const CUtensorMap* pa = it < NK2 ? &mapH : &mapO;
                const CUtensorMap* pb = it < NK2 ? &mapW2 : &mapWo;
                int k = (it < NK2 ? it : it - NK2) * 64;
                tma_load_2d(a, pa, bar_full + 8 * s, k, m0);
                tma_load_2d(a + 8192, pb, bar_full + 8 * s, n0, k);
                tma_load_2d(a + 8192 + 8192, pb, bar_full + 8 * s, n0 + 64, k);
            }
        }
    } else {
        float acc[64], acc2[64];
        int warp = tid >> 5, lane = tid & 31;
        int r = warp * 16 + (lane >> 2);
        uint32_t xv[32], bv[16];
#pragma unroll
        for (int j = 0; j < 16; j++) {
            int c = n0 + j * 8 + (lane & 3) * 2;
            bv[j] = *reinterpret_cast<const uint32_t*>(b2 + c);
            xv[j * 2] = *reinterpret_cast<const uint32_t*>(x + (size_t)(m0 + r) * DM + c);
            xv[j * 2 + 1] = *reinterpret_cast<const uint32_t*>(x + (size_t)(m0 + r + 8) * DM + c);
        }
        for (int it = 0; it < NK2; it++) {
            int s = it % F_STAGES;
            uint32_t ph = (it / F_STAGES) & 1;
            mbar_wait(bar_full + 8 * s, ph);
            uint32_t a = sbase + s * G_STAGE_BYTES;
            uint32_t b = a + 8192;
            wgmma_fence();
#pragma unroll
            for (int kk = 0; kk < 4; kk++)
                wgmma_m64n128k16_ss<0, 1>(acc2, make_desc(a + kk * 32, 16, 1024), make_desc(b + kk * 2048, 8192, 1024), (it | kk) != 0);
            wgmma_commit();
            wgmma_wait<1>();
            if (it > 0 && lane == 0) mbar_arrive(bar_empty + 8 * ((it - 1) % F_STAGES));
        }
        for (int it = NK2; it < NK1 + NK2; it++) {
            int s = it % F_STAGES;
            uint32_t ph = (it / F_STAGES) & 1;
            mbar_wait(bar_full + 8 * s, ph);
            uint32_t a = sbase + s * G_STAGE_BYTES;
            uint32_t b = a + 8192;
            wgmma_fence();
#pragma unroll
            for (int kk = 0; kk < 4; kk++)
                wgmma_m64n128k16_ss<0, 1>(acc, make_desc(a + kk * 32, 16, 1024), make_desc(b + kk * 2048, 8192, 1024), ((it - NK2) | kk) != 0);
            wgmma_commit();
            wgmma_wait<1>();
            if (lane == 0) mbar_arrive(bar_empty + 8 * ((it - 1) % F_STAGES));
        }
        wgmma_wait<0>();
#pragma unroll
        for (int j = 0; j < 16; j++) {
            float2 bf = __bfloat1622float2(*reinterpret_cast<const __nv_bfloat162*>(&bv[j]));
            uint32_t a = sbase + r * 256 + ((j ^ (r & 7)) << 4) + (lane & 3) * 4;
#pragma unroll
            for (int h = 0; h < 2; h++) {
                float2 xf = __bfloat1622float2(*reinterpret_cast<const __nv_bfloat162*>(&xv[j * 2 + h]));
                float g0 = acc2[j * 4 + h * 2 + 0] + bf.x, g1 = acc2[j * 4 + h * 2 + 1] + bf.y;
                g0 = __fdividef(g0, 1.f + __expf(-g0)); g1 = __fdividef(g1, 1.f + __expf(-g1));
                st_shared_u32(a + h * 2048, pack_bf16(xf.x + acc[j * 4 + h * 2 + 0] * g0, xf.y + acc[j * 4 + h * 2 + 1] * g1));
            }
        }
        named_sync(1, 128);
#pragma unroll
        for (int i = 0; i < 8; i++) {
            int idx = i * 128 + tid;
            int rr = idx >> 4, ch = idx & 15;
            uint4 v = ld_shared_v4(sbase + rr * 256 + ((ch ^ (rr & 7)) << 4));
            *reinterpret_cast<uint4*>(out + (size_t)(m0 + rr) * DM + n0 + ch * 8) = v;
        }
    }
}

typedef CUresult (*EncodeFn)(CUtensorMap*, CUtensorMapDataType, cuuint32_t, void*, const cuuint64_t*, const cuuint64_t*,
                             const cuuint32_t*, const cuuint32_t*, CUtensorMapInterleave, CUtensorMapSwizzle,
                             CUtensorMapL2promotion, CUtensorMapFloatOOBfill);

static void make_map(EncodeFn fn, CUtensorMap* m, const void* ptr, uint64_t inner, uint64_t outer,
                     uint32_t box_inner, uint32_t box_outer) {
    cuuint64_t dims[2] = {inner, outer};
    cuuint64_t strides[1] = {inner * 2};
    cuuint32_t box[2] = {box_inner, box_outer};
    cuuint32_t es[2] = {1, 1};
    fn(m, CU_TENSOR_MAP_DATA_TYPE_BFLOAT16, 2, const_cast<void*>(ptr), dims, strides, box, es,
       CU_TENSOR_MAP_INTERLEAVE_NONE, CU_TENSOR_MAP_SWIZZLE_128B, CU_TENSOR_MAP_L2_PROMOTION_L2_256B,
       CU_TENSOR_MAP_FLOAT_OOB_FILL_NONE);
}

extern "C" void kernel_launch(void* const* d_in, const int* in_sizes, int n_in, void* d_out, int out_size) {
    const bf16* x  = (const bf16*)d_in[0];
    const bf16* kc = (const bf16*)d_in[1];
    const bf16* vc = (const bf16*)d_in[2];
    const bf16* wq = (const bf16*)d_in[3];
    const bf16* wo = (const bf16*)d_in[4];
    const bf16* w1 = (const bf16*)d_in[6];
    const bf16* b1 = (const bf16*)d_in[7];
    const bf16* w2 = (const bf16*)d_in[8];
    const bf16* b2 = (const bf16*)d_in[9];
    bf16* out = (bf16*)d_out;

    static bool inited = false;
    static CUtensorMap mXn, mY, mWq, mW1, mQ, mK, mV, mO, mWo, mH, mW2;
    static void *pq, *ph;
    static cudaStream_t s2;
    static cudaEvent_t evFork, evJoin;
    if (!inited) {
        EncodeFn fn = nullptr;
        cudaDriverEntryPointQueryResult qres;
        cudaGetDriverEntryPoint("cuTensorMapEncodeTiled", (void**)&fn, cudaEnableDefault, &qres);
        void *pxn, *py, *po;
        cudaGetSymbolAddress(&pxn, g_xn); cudaGetSymbolAddress(&py, g_y); cudaGetSymbolAddress(&pq, g_q);
        cudaGetSymbolAddress(&ph, g_h); cudaGetSymbolAddress(&po, g_o);
        make_map(fn, &mXn, pxn, DM, SEQ, 64, 128);
        make_map(fn, &mY, py, DM, SEQ, 64, 64);
        make_map(fn, &mWq, wq, HD, DM, 64, 64);
        make_map(fn, &mW1, w1, FF, DM, 64, 64);
        make_map(fn, &mK, kc, DH, NH * SEQ, 64, 128);
        make_map(fn, &mV, vc, DH, NH * SEQ, 64, 128);
        make_map(fn, &mO, po, HD, SEQ, 64, 64);
        make_map(fn, &mWo, wo, DM, HD, 64, 64);
        make_map(fn, &mH, ph, FF, SEQ, 64, 64);
        make_map(fn, &mW2, w2, DM, FF, 64, 64);
        cudaFuncSetAttribute(mlp1_kernel, cudaFuncAttributeMaxDynamicSharedMemorySize, M1_SMEM);
        cudaFuncSetAttribute(final_kernel, cudaFuncAttributeMaxDynamicSharedMemorySize, F_SMEM);
        cudaFuncSetAttribute(attn_kernel, cudaFuncAttributeMaxDynamicSharedMemorySize, A_SMEM);
        cudaStreamCreateWithFlags(&s2, cudaStreamNonBlocking);
        cudaEventCreateWithFlags(&evFork, cudaEventDisableTiming);
        cudaEventCreateWithFlags(&evJoin, cudaEventDisableTiming);
        inited = true;
    }

    ln_kernel<<<SEQ / 8, 256>>>(x);
    cudaEventRecord(evFork, cudaStreamPerThread);
    attn_kernel<<<dim3(SEQ / 128, NH), 384, A_SMEM>>>(mXn, mWq, mK, mV);
    cudaStreamWaitEvent(s2, evFork, 0);
    mlp1_kernel<<<dim3((FF + 127) / 128, SEQ / 64), 256, M1_SMEM, s2>>>(mY, mW1, (bf16*)ph, b1);
    cudaEventRecord(evJoin, s2);
    cudaStreamWaitEvent(cudaStreamPerThread, evJoin, 0);
    final_kernel<<<dim3(DM / 128, SEQ / 64), 256, F_SMEM>>>(mO, mWo, mH, mW2, x, b2, out);
}
```

```cpp
#include <cuda_runtime.h>
#include <cuda_bf16.h>
#include <cuda.h>
#include <stdint.h>

typedef __nv_bfloat16 bf16;

constexpr int SEQ = 2048;
constexpr int DM  = 512;
constexpr int NH  = 32;
constexpr int DH  = 128;
constexpr int HD  = NH * DH;
constexpr int FF  = 1376;

__device__ bf16 g_xn[SEQ * DM];
__device__ bf16 g_y [SEQ * DM];
__device__ bf16 g_q [SEQ * HD];
__device__ bf16 g_h [SEQ * FF];
__device__ bf16 g_o [SEQ * HD];
__device__ bf16 g_g [SEQ * DM];

__device__ __forceinline__ uint32_t smem_u32(const void* p) {
    return (uint32_t)__cvta_generic_to_shared(p);
}
__device__ __forceinline__ void mbar_init(uint32_t bar, uint32_t count) {
    asm volatile("mbarrier.init.shared::cta.b64 [%0], %1;" :: "r"(bar), "r"(count) : "memory");
}
__device__ __forceinline__ void mbar_arrive(uint32_t bar) {
    asm volatile("mbarrier.arrive.shared::cta.b64 _, [%0];" :: "r"(bar) : "memory");
}
__device__ __forceinline__ void mbar_expect_tx(uint32_t bar, uint32_t bytes) {
    asm volatile("mbarrier.arrive.expect_tx.shared::cta.b64 _, [%0], %1;" :: "r"(bar), "r"(bytes) : "memory");
}
__device__ __forceinline__ void mbar_wait(uint32_t bar, uint32_t parity) {
    asm volatile(
        "{\n"
        ".reg .pred p;\n"
        "LAB_WAIT:\n"
        "mbarrier.try_wait.parity.shared::cta.b64 p, [%0], %1;\n"
        "@p bra DONE;\n"
        "bra LAB_WAIT;\n"
        "DONE:\n"
        "}\n" :: "r"(bar), "r"(parity) : "memory");
}
__device__ __forceinline__ void tma_load_2d(uint32_t dst, const CUtensorMap* map, uint32_t bar, int c0, int c1) {
    asm volatile(
        "cp.async.bulk.tensor.2d.shared::cluster.global.mbarrier::complete_tx::bytes [%0], [%1, {%3, %4}], [%2];"
        :: "r"(dst), "l"((uint64_t)map), "r"(bar), "r"(c0), "r"(c1) : "memory");
}
__device__ __forceinline__ void wgmma_fence() { asm volatile("wgmma.fence.sync.aligned;" ::: "memory"); }
__device__ __forceinline__ void wgmma_commit() { asm volatile("wgmma.commit_group.sync.aligned;" ::: "memory"); }
template <int N> __device__ __forceinline__ void wgmma_wait() {
    asm volatile("wgmma.wait_group.sync.aligned %0;" :: "n"(N) : "memory");
}
template <int R> __device__ __forceinline__ void reg_alloc() {
    asm volatile("setmaxnreg.inc.sync.aligned.u32 %0;" :: "n"(R));
}
template <int R> __device__ __forceinline__ void reg_dealloc() {
    asm volatile("setmaxnreg.dec.sync.aligned.u32 %0;" :: "n"(R));
}
__device__ __forceinline__ void fence_barrier_init() {
    asm volatile("fence.mbarrier_init.release.cluster;" ::: "memory");
}
__device__ __forceinline__ void fence_proxy_async() {
    asm volatile("fence.proxy.async.shared::cta;" ::: "memory");
}

__device__ __forceinline__ void named_sync(int id, int n) {
    asm volatile("bar.sync %0, %1;" :: "r"(id), "r"(n) : "memory");
}
__device__ __forceinline__ void named_arrive(int id, int n) {
    asm volatile("bar.arrive %0, %1;" :: "r"(id), "r"(n) : "memory");
}
__device__ __forceinline__ float fast_exp2(float x) {
    float y;
    asm("ex2.approx.ftz.f32 %0, %1;" : "=f"(y) : "f"(x));
    return y;
}

__device__ __forceinline__ void st_shared_u32(uint32_t a, uint32_t v) {
    asm volatile("st.shared.u32 [%0], %1;" :: "r"(a), "r"(v) : "memory");
}
__device__ __forceinline__ uint4 ld_shared_v4(uint32_t a) {
    uint4 v;
    asm volatile("ld.shared.v4.u32 {%0,%1,%2,%3}, [%4];" : "=r"(v.x), "=r"(v.y), "=r"(v.z), "=r"(v.w) : "r"(a) : "memory");
    return v;
}

__device__ __forceinline__ uint64_t make_desc(uint32_t addr, uint32_t lbo_bytes, uint32_t sbo_bytes) {
    uint64_t d = 0;
    d |= (uint64_t)((addr & 0x3FFFF) >> 4);
    d |= (uint64_t)((lbo_bytes & 0x3FFFF) >> 4) << 16;
    d |= (uint64_t)((sbo_bytes & 0x3FFFF) >> 4) << 32;
    d |= (uint64_t)1 << 62;
    return d;
}

template <int TA, int TB>
__device__ __forceinline__ void wgmma_m64n128k16_ss(float (&d)[64], uint64_t da, uint64_t db, int scale_d) {
    asm volatile(
        "{\n.reg .pred p;\nsetp.ne.b32 p, %66, 0;\n"
        "wgmma.mma_async.sync.aligned.m64n128k16.f32.bf16.bf16 "
        "{%0,%1,%2,%3,%4,%5,%6,%7,%8,%9,%10,%11,%12,%13,%14,%15,"
        "%16,%17,%18,%19,%20,%21,%22,%23,%24,%25,%26,%27,%28,%29,%30,%31,"
        "%32,%33,%34,%35,%36,%37,%38,%39,%40,%41,%42,%43,%44,%45,%46,%47,"
        "%48,%49,%50,%51,%52,%53,%54,%55,%56,%57,%58,%59,%60,%61,%62,%63},"
        " %64, %65, p, 1, 1, %67, %68;\n}\n"
        : "+f"(d[0]), "+f"(d[1]), "+f"(d[2]), "+f"(d[3]), "+f"(d[4]), "+f"(d[5]), "+f"(d[6]), "+f"(d[7]),
          "+f"(d[8]), "+f"(d[9]), "+f"(d[10]), "+f"(d[11]), "+f"(d[12]), "+f"(d[13]), "+f"(d[14]), "+f"(d[15]),
          "+f"(d[16]), "+f"(d[17]), "+f"(d[18]), "+f"(d[19]), "+f"(d[20]), "+f"(d[21]), "+f"(d[22]), "+f"(d[23]),
          "+f"(d[24]), "+f"(d[25]), "+f"(d[26]), "+f"(d[27]), "+f"(d[28]), "+f"(d[29]), "+f"(d[30]), "+f"(d[31]),
          "+f"(d[32]), "+f"(d[33]), "+f"(d[34]), "+f"(d[35]), "+f"(d[36]), "+f"(d[37]), "+f"(d[38]), "+f"(d[39]),
          "+f"(d[40]), "+f"(d[41]), "+f"(d[42]), "+f"(d[43]), "+f"(d[44]), "+f"(d[45]), "+f"(d[46]), "+f"(d[47]),
          "+f"(d[48]), "+f"(d[49]), "+f"(d[50]), "+f"(d[51]), "+f"(d[52]), "+f"(d[53]), "+f"(d[54]), "+f"(d[55]),
          "+f"(d[56]), "+f"(d[57]), "+f"(d[58]), "+f"(d[59]), "+f"(d[60]), "+f"(d[61]), "+f"(d[62]), "+f"(d[63])
        : "l"(da), "l"(db), "r"(scale_d), "n"(TA), "n"(TB));
}

template <int TB>
__device__ __forceinline__ void wgmma_m64n128k16_rs(float (&d)[64], uint32_t a0, uint32_t a1, uint32_t a2, uint32_t a3,
                                                    uint64_t db, int scale_d) {
    asm volatile(
        "{\n.reg .pred p;\nsetp.ne.b32 p, %69, 0;\n"
        "wgmma.mma_async.sync.aligned.m64n128k16.f32.bf16.bf16 "
        "{%0,%1,%2,%3,%4,%5,%6,%7,%8,%9,%10,%11,%12,%13,%14,%15,"
        "%16,%17,%18,%19,%20,%21,%22,%23,%24,%25,%26,%27,%28,%29,%30,%31,"
        "%32,%33,%34,%35,%36,%37,%38,%39,%40,%41,%42,%43,%44,%45,%46,%47,"
        "%48,%49,%50,%51,%52,%53,%54,%55,%56,%57,%58,%59,%60,%61,%62,%63},"
        " {%64,%65,%66,%67}, %68, p, 1, 1, %70;\n}\n"
        : "+f"(d[0]), "+f"(d[1]), "+f"(d[2]), "+f"(d[3]), "+f"(d[4]), "+f"(d[5]), "+f"(d[6]), "+f"(d[7]),
          "+f"(d[8]), "+f"(d[9]), "+f"(d[10]), "+f"(d[11]), "+f"(d[12]), "+f"(d[13]), "+f"(d[14]), "+f"(d[15]),
          "+f"(d[16]), "+f"(d[17]), "+f"(d[18]), "+f"(d[19]), "+f"(d[20]), "+f"(d[21]), "+f"(d[22]), "+f"(d[23]),
          "+f"(d[24]), "+f"(d[25]), "+f"(d[26]), "+f"(d[27]), "+f"(d[28]), "+f"(d[29]), "+f"(d[30]), "+f"(d[31]),
          "+f"(d[32]), "+f"(d[33]), "+f"(d[34]), "+f"(d[35]), "+f"(d[36]), "+f"(d[37]), "+f"(d[38]), "+f"(d[39]),
          "+f"(d[40]), "+f"(d[41]), "+f"(d[42]), "+f"(d[43]), "+f"(d[44]), "+f"(d[45]), "+f"(d[46]), "+f"(d[47]),
          "+f"(d[48]), "+f"(d[49]), "+f"(d[50]), "+f"(d[51]), "+f"(d[52]), "+f"(d[53]), "+f"(d[54]), "+f"(d[55]),
          "+f"(d[56]), "+f"(d[57]), "+f"(d[58]), "+f"(d[59]), "+f"(d[60]), "+f"(d[61]), "+f"(d[62]), "+f"(d[63])
        : "r"(a0), "r"(a1), "r"(a2), "r"(a3), "l"(db), "r"(scale_d), "n"(TB));
}

__device__ __forceinline__ uint32_t pack_bf16(float lo, float hi) {
    __nv_bfloat162 v = __floats2bfloat162_rn(lo, hi);
    return *reinterpret_cast<uint32_t*>(&v);
}

__global__ void __launch_bounds__(256) ln_kernel(const bf16* __restrict__ x) {
    int warp = threadIdx.x >> 5, lane = threadIdx.x & 31;
    int row = blockIdx.x * 8 + warp;
    const uint4* src = reinterpret_cast<const uint4*>(x + (size_t)row * DM);
    float v[16];
#pragma unroll
    for (int i = 0; i < 2; i++) {
        uint4 u = src[lane + i * 32];
        const __nv_bfloat162* h = reinterpret_cast<const __nv_bfloat162*>(&u);
#pragma unroll
        for (int j = 0; j < 4; j++) {
            float2 f = __bfloat1622float2(h[j]);
            v[i * 8 + j * 2] = f.x; v[i * 8 + j * 2 + 1] = f.y;
        }
    }
#pragma unroll
    for (int pass = 0; pass < 2; pass++) {
        float s = 0.f;
#pragma unroll
        for (int i = 0; i < 16; i++) s += v[i];
#pragma unroll
        for (int o = 16; o > 0; o >>= 1) s += __shfl_xor_sync(0xffffffffu, s, o);
        float mean = s * (1.f / DM);
        float q = 0.f;
#pragma unroll
        for (int i = 0; i < 16; i++) { float d = v[i] - mean; q += d * d; }
#pragma unroll
        for (int o = 16; o > 0; o >>= 1) q += __shfl_xor_sync(0xffffffffu, q, o);
        float rstd = 1.0f / sqrtf(q * (1.f / DM) + 1e-5f);
        bf16* dst = (pass == 0 ? g_xn : g_y) + (size_t)row * DM;
#pragma unroll
        for (int i = 0; i < 2; i++) {
            uint4 u;
            uint32_t* w = reinterpret_cast<uint32_t*>(&u);
#pragma unroll
            for (int j = 0; j < 4; j++) {
                __nv_bfloat162 h = __floats2bfloat162_rn((v[i * 8 + j * 2] - mean) * rstd, (v[i * 8 + j * 2 + 1] - mean) * rstd);
                w[j] = *reinterpret_cast<uint32_t*>(&h);
                float2 f = __bfloat1622float2(h);
                v[i * 8 + j * 2] = f.x; v[i * 8 + j * 2 + 1] = f.y;
            }
            reinterpret_cast<uint4*>(dst)[lane + i * 32] = u;
        }
    }
}

constexpr int G_STAGE_BYTES = 8192 + 16384;

__device__ __forceinline__ float gelu_tanh(float x) {
    float u = 0.7978845608028654f * (x + 0.044715f * x * x * x);
    float t = 1.f - __fdividef(2.f, 1.f + __expf(2.f * u));
    return 0.5f * x * (1.f + t);
}

__device__ __forceinline__ float silu_f(float g) { return __fdividef(g, 1.f + __expf(-g)); }

constexpr int M1_STAGES = 4;
constexpr int M1_SMEM = M1_STAGES * G_STAGE_BYTES + 1024 + 256;
template <int MODE, int NN, int KK>
__global__ void __launch_bounds__(256, 2)
mlp1_kernel(const __grid_constant__ CUtensorMap mapA, const __grid_constant__ CUtensorMap mapB,
            bf16* __restrict__ C, const bf16* __restrict__ bias) {
    extern __shared__ uint8_t smem_raw[];
    uint32_t sbase = (smem_u32(smem_raw) + 1023) & ~1023u;
    uint32_t bar_full = sbase + M1_STAGES * G_STAGE_BYTES;
    uint32_t bar_empty = bar_full + 8 * M1_STAGES;
    int wg = threadIdx.x >> 7;
    int tid = threadIdx.x & 127;
    int m0 = blockIdx.y * 64, n0 = blockIdx.x * 128;
    constexpr int nk = (KK + 63) / 64;

    if (threadIdx.x == 0) {
        for (int i = 0; i < M1_STAGES; i++) { mbar_init(bar_full + 8 * i, 1); mbar_init(bar_empty + 8 * i, 4); }
        fence_barrier_init();
    }
    __syncthreads();

    if (wg == 0) {
        if (tid == 0) {
            for (int it = 0; it < nk; it++) {
                int s = it % M1_STAGES;
                uint32_t ph = (it / M1_STAGES) & 1;
                mbar_wait(bar_empty + 8 * s, ph ^ 1);
                mbar_expect_tx(bar_full + 8 * s, G_STAGE_BYTES);
                uint32_t a = sbase + s * G_STAGE_BYTES;
                tma_load_2d(a, &mapA, bar_full + 8 * s, it * 64, m0);
                tma_load_2d(a + 8192, &mapB, bar_full + 8 * s, n0, it * 64);
                tma_load_2d(a + 8192 + 8192, &mapB, bar_full + 8 * s, n0 + 64, it * 64);
            }
        }
    } else {
        float acc[64];
        int warp = tid >> 5, lane = tid & 31;
        uint32_t bv[16];
#pragma unroll
        for (int j = 0; j < 16; j++) {
            int c = min(n0 + j * 8 + (lane & 3) * 2, NN - 2);
            bv[j] = *reinterpret_cast<const uint32_t*>(bias + c);
        }
        for (int it = 0; it < nk; it++) {
            int s = it % M1_STAGES;
            uint32_t ph = (it / M1_STAGES) & 1;
            mbar_wait(bar_full + 8 * s, ph);
            uint32_t a = sbase + s * G_STAGE_BYTES;
            uint32_t b = a + 8192;
            wgmma_fence();
#pragma unroll
            for (int kk = 0; kk < 4; kk++)
                wgmma_m64n128k16_ss<0, 1>(acc, make_desc(a + kk * 32, 16, 1024), make_desc(b + kk * 2048, 8192, 1024), (it | kk) != 0);
            wgmma_commit();
            wgmma_wait<1>();
            if (it > 0 && lane == 0) mbar_arrive(bar_empty + 8 * ((it - 1) % M1_STAGES));
        }
        wgmma_wait<0>();
        int r = warp * 16 + (lane >> 2);
#pragma unroll
        for (int j = 0; j < 16; j++) {
            float2 bf = __bfloat1622float2(*reinterpret_cast<const __nv_bfloat162*>(&bv[j]));
            float b0 = bf.x, b1 = bf.y;
            uint32_t a = sbase + r * 256 + ((j ^ (r & 7)) << 4) + (lane & 3) * 4;
            if (MODE == 1) {
                st_shared_u32(a, pack_bf16(gelu_tanh(acc[j * 4 + 0] + b0), gelu_tanh(acc[j * 4 + 1] + b1)));
                st_shared_u32(a + 2048, pack_bf16(gelu_tanh(acc[j * 4 + 2] + b0), gelu_tanh(acc[j * 4 + 3] + b1)));
            } else {
                st_shared_u32(a, pack_bf16(silu_f(acc[j * 4 + 0] + b0), silu_f(acc[j * 4 + 1] + b1)));
                st_shared_u32(a + 2048, pack_bf16(silu_f(acc[j * 4 + 2] + b0), silu_f(acc[j * 4 + 3] + b1)));
            }
        }
        named_sync(1, 128);
#pragma unroll
        for (int i = 0; i < 8; i++) {
            int idx = i * 128 + tid;
            int rr = idx >> 4, ch = idx & 15;
            uint4 v = ld_shared_v4(sbase + rr * 256 + ((ch ^ (rr & 7)) << 4));
            if (n0 + ch * 8 < NN)
                *reinterpret_cast<uint4*>(C + (size_t)(m0 + rr) * NN + n0 + ch * 8) = v;
        }
    }
}

constexpr int A_KV_STAGES = 2;
constexpr int A_TILE_BYTES = 128 * 128 * 2;
constexpr int A_SMEM = A_TILE_BYTES * (1 + 2 * A_KV_STAGES) + 1024 + 256;

__global__ void __launch_bounds__(384, 1)
attn_kernel(const __grid_constant__ CUtensorMap mapXn, const __grid_constant__ CUtensorMap mapWq,
            const __grid_constant__ CUtensorMap mapK, const __grid_constant__ CUtensorMap mapV) {
    extern __shared__ uint8_t smem_raw[];
    uint32_t sbase = (smem_u32(smem_raw) + 1023) & ~1023u;
    uint32_t sQ = sbase;
    uint32_t sK = sQ + A_TILE_BYTES;
    uint32_t sV = sK + A_KV_STAGES * A_TILE_BYTES;
    uint32_t bars = sV + A_KV_STAGES * A_TILE_BYTES;
    uint32_t bar_pf = bars, bar_pe = bars + 32;
    uint32_t bar_kf = bars + 64, bar_ke = bar_kf + 8 * A_KV_STAGES;
    uint32_t bar_vf = bar_ke + 8 * A_KV_STAGES, bar_ve = bar_vf + 8 * A_KV_STAGES;
    int wg = threadIdx.x >> 7;
    int tid = threadIdx.x & 127;
    int qt = blockIdx.x, head = blockIdx.y;
    constexpr int NT = SEQ / 128;

    if (threadIdx.x == 0) {
        for (int i = 0; i < 4; i++) { mbar_init(bar_pf + 8 * i, 1); mbar_init(bar_pe + 8 * i, 8); }
        for (int i = 0; i < A_KV_STAGES; i++) {
            mbar_init(bar_kf + 8 * i, 1); mbar_init(bar_ke + 8 * i, 8);
            mbar_init(bar_vf + 8 * i, 1); mbar_init(bar_ve + 8 * i, 8);
        }
        fence_barrier_init();
    }
    __syncthreads();

    if (wg == 0) {
        reg_dealloc<40>();
        if (tid == 0) {
            for (int i = 0; i < 8; i++) {
                int b = i & 3;
                uint32_t buf = sK + b * A_TILE_BYTES;
                mbar_wait(bar_pe + 8 * b, ((i >> 2) & 1) ^ 1);
                mbar_expect_tx(bar_pf + 8 * b, A_TILE_BYTES);
                tma_load_2d(buf, &mapXn, bar_pf + 8 * b, i * 64, qt * 128);
                tma_load_2d(buf + 16384, &mapWq, bar_pf + 8 * b, head * DH, i * 64);
                tma_load_2d(buf + 16384 + 8192, &mapWq, bar_pf + 8 * b, head * DH + 64, i * 64);
            }
            for (int it = 0; it < NT; it++) {
                int s = it % A_KV_STAGES;
                uint32_t ph = (it / A_KV_STAGES) & 1;
                int row = head * SEQ + it * 128;
                if (it < A_KV_STAGES) mbar_wait(bar_pe + 8 * s, 1);
                else mbar_wait(bar_ke + 8 * s, ph ^ 1);
                mbar_expect_tx(bar_kf + 8 * s, A_TILE_BYTES);
                tma_load_2d(sK + s * A_TILE_BYTES, &mapK, bar_kf + 8 * s, 0, row);
                tma_load_2d(sK + s * A_TILE_BYTES + 16384, &mapK, bar_kf + 8 * s, 64, row);
                if (it < A_KV_STAGES) mbar_wait(bar_pe + 8 * (A_KV_STAGES + s), 1);
                else mbar_wait(bar_ve + 8 * s, ph ^ 1);
                mbar_expect_tx(bar_vf + 8 * s, A_TILE_BYTES);
                tma_load_2d(sV + s * A_TILE_BYTES, &mapV, bar_vf + 8 * s, 0, row);
                tma_load_2d(sV + s * A_TILE_BYTES + 16384, &mapV, bar_vf + 8 * s, 64, row);
            }
        }
    } else {
        reg_alloc<232>();
        int cw = wg - 1;
        int warp = tid >> 5, lane = tid & 31;
        float o[64];
        for (int i = 0; i < 8; i++) {
            int b = i & 3;
            uint32_t buf = sK + b * A_TILE_BYTES;
            mbar_wait(bar_pf + 8 * b, (i >> 2) & 1);
            wgmma_fence();
#pragma unroll
            for (int kk = 0; kk < 4; kk++)
                wgmma_m64n128k16_ss<0, 1>(o, make_desc(buf + cw * 8192 + kk * 32, 16, 1024),
                                          make_desc(buf + 16384 + kk * 2048, 8192, 1024), (i | kk) != 0);
            wgmma_commit();
            wgmma_wait<0>();
            if (lane == 0) mbar_arrive(bar_pe + 8 * b);
        }
        {
            int r = cw * 64 + warp * 16 + (lane >> 2);
#pragma unroll
            for (int j = 0; j < 16; j++) {
                uint32_t a = sQ + (j >> 3) * 16384 + r * 128 + (((j & 7) ^ (r & 7)) << 4) + (lane & 3) * 4;
                st_shared_u32(a, pack_bf16(o[j * 4 + 0], o[j * 4 + 1]));
                st_shared_u32(a + 1024, pack_bf16(o[j * 4 + 2], o[j * 4 + 3]));
            }
            fence_proxy_async();
            named_sync(3 + cw, 128);
        }
#pragma unroll
        for (int i = 0; i < 64; i++) o[i] = 0.f;
        float m0 = -INFINITY, m1 = -INFINITY, l0 = 0.f, l1 = 0.f;
        const float sc = 0.08838834764831845f * 1.4426950408889634f;
        if (cw == 1) named_arrive(1, 256);
        uint32_t qa = sQ + cw * 8192;
        float sacc[64];
        uint32_t p[32];
        mbar_wait(bar_kf, 0);
        named_sync(1 + cw, 256);
        wgmma_fence();
#pragma unroll
        for (int kk = 0; kk < 8; kk++) {
            uint32_t off = (kk >> 2) * 16384 + (kk & 3) * 32;
            wgmma_m64n128k16_ss<0, 0>(sacc, make_desc(qa + off, 16, 1024), make_desc(sK + off, 16, 1024), kk != 0);
        }
        wgmma_commit();
        named_arrive(1 + (cw ^ 1), 256);
        wgmma_wait<0>();
        if (lane == 0) mbar_arrive(bar_ke);
        {
            float mx0 = -INFINITY, mx1 = -INFINITY;
#pragma unroll
            for (int j = 0; j < 16; j++) {
                mx0 = fmaxf(mx0, fmaxf(sacc[j * 4 + 0], sacc[j * 4 + 1]));
                mx1 = fmaxf(mx1, fmaxf(sacc[j * 4 + 2], sacc[j * 4 + 3]));
            }
            mx0 = fmaxf(mx0, __shfl_xor_sync(0xffffffffu, mx0, 1));
            mx0 = fmaxf(mx0, __shfl_xor_sync(0xffffffffu, mx0, 2));
            mx1 = fmaxf(mx1, __shfl_xor_sync(0xffffffffu, mx1, 1));
            mx1 = fmaxf(mx1, __shfl_xor_sync(0xffffffffu, mx1, 2));
            m0 = mx0; m1 = mx1;
            float ms0 = mx0 * sc, ms1 = mx1 * sc;
#pragma unroll
            for (int j = 0; j < 16; j++) {
                float p0 = fast_exp2(sacc[j * 4 + 0] * sc - ms0);
                float p1 = fast_exp2(sacc[j * 4 + 1] * sc - ms0);
                float p2 = fast_exp2(sacc[j * 4 + 2] * sc - ms1);
                float p3 = fast_exp2(sacc[j * 4 + 3] * sc - ms1);
                l0 += p0 + p1; l1 += p2 + p3;
                p[j * 2 + 0] = pack_bf16(p0, p1);
                p[j * 2 + 1] = pack_bf16(p2, p3);
            }
        }
        for (int it = 1; it < NT; it++) {
            int s = it % A_KV_STAGES;
            uint32_t ph = (it / A_KV_STAGES) & 1;
            int sp = (it - 1) % A_KV_STAGES;
            uint32_t php = ((it - 1) / A_KV_STAGES) & 1;
            mbar_wait(bar_kf + 8 * s, ph);
            named_sync(1 + cw, 256);
            uint32_t kb = sK + s * A_TILE_BYTES;
            wgmma_fence();
#pragma unroll
            for (int kk = 0; kk < 8; kk++) {
                uint32_t off = (kk >> 2) * 16384 + (kk & 3) * 32;
                wgmma_m64n128k16_ss<0, 0>(sacc, make_desc(qa + off, 16, 1024), make_desc(kb + off, 16, 1024), kk != 0);
            }
            wgmma_commit();
            mbar_wait(bar_vf + 8 * sp, php);
            uint32_t vb = sV + sp * A_TILE_BYTES;
#pragma unroll
            for (int kk = 0; kk < 8; kk++) {
                wgmma_m64n128k16_rs<1>(o, p[kk * 4 + 0], p[kk * 4 + 1], p[kk * 4 + 2], p[kk * 4 + 3],
                                       make_desc(vb + kk * 2048, 16384, 1024), 1);
            }
            wgmma_commit();
            named_arrive(1 + (cw ^ 1), 256);
            wgmma_wait<1>();
            if (lane == 0) mbar_arrive(bar_ke + 8 * s);
            float mx0 = m0, mx1 = m1;
#pragma unroll
            for (int j = 0; j < 16; j++) {
                mx0 = fmaxf(mx0, fmaxf(sacc[j * 4 + 0], sacc[j * 4 + 1]));
                mx1 = fmaxf(mx1, fmaxf(sacc[j * 4 + 2], sacc[j * 4 + 3]));
            }
            mx0 = fmaxf(mx0, __shfl_xor_sync(0xffffffffu, mx0, 1));
            mx0 = fmaxf(mx0, __shfl_xor_sync(0xffffffffu, mx0, 2));
            mx1 = fmaxf(mx1, __shfl_xor_sync(0xffffffffu, mx1, 1));
            mx1 = fmaxf(mx1, __shfl_xor_sync(0xffffffffu, mx1, 2));
            float c0 = fast_exp2((m0 - mx0) * sc), c1 = fast_exp2((m1 - mx1) * sc);
            m0 = mx0; m1 = mx1;
            float ms0 = mx0 * sc, ms1 = mx1 * sc;
            float rs0 = 0.f, rs1 = 0.f;
#pragma unroll
            for (int j = 0; j < 16; j++) {
                sacc[j * 4 + 0] = fast_exp2(sacc[j * 4 + 0] * sc - ms0);
                sacc[j * 4 + 1] = fast_exp2(sacc[j * 4 + 1] * sc - ms0);
                sacc[j * 4 + 2] = fast_exp2(sacc[j * 4 + 2] * sc - ms1);
                sacc[j * 4 + 3] = fast_exp2(sacc[j * 4 + 3] * sc - ms1);
                rs0 += sacc[j * 4 + 0] + sacc[j * 4 + 1]; rs1 += sacc[j * 4 + 2] + sacc[j * 4 + 3];
            }
            l0 = l0 * c0 + rs0; l1 = l1 * c1 + rs1;
            wgmma_wait<0>();
            if (lane == 0) mbar_arrive(bar_ve + 8 * sp);
#pragma unroll
            for (int j = 0; j < 16; j++) {
                o[j * 4 + 0] *= c0; o[j * 4 + 1] *= c0; o[j * 4 + 2] *= c1; o[j * 4 + 3] *= c1;
                p[j * 2 + 0] = pack_bf16(sacc[j * 4 + 0], sacc[j * 4 + 1]);
                p[j * 2 + 1] = pack_bf16(sacc[j * 4 + 2], sacc[j * 4 + 3]);
            }
        }
        {
            int sp = (NT - 1) % A_KV_STAGES;
            uint32_t php = ((NT - 1) / A_KV_STAGES) & 1;
            mbar_wait(bar_vf + 8 * sp, php);
            uint32_t vb = sV + sp * A_TILE_BYTES;
            wgmma_fence();
#pragma unroll
            for (int kk = 0; kk < 8; kk++) {
                wgmma_m64n128k16_rs<1>(o, p[kk * 4 + 0], p[kk * 4 + 1], p[kk * 4 + 2], p[kk * 4 + 3],
                                       make_desc(vb + kk * 2048, 16384, 1024), 1);
            }
            wgmma_commit();
            wgmma_wait<0>();
        }
        l0 += __shfl_xor_sync(0xffffffffu, l0, 1);
        l0 += __shfl_xor_sync(0xffffffffu, l0, 2);
        l1 += __shfl_xor_sync(0xffffffffu, l1, 1);
        l1 += __shfl_xor_sync(0xffffffffu, l1, 2);
        float i0 = 1.f / l0, i1 = 1.f / l1;
        {
            int r = cw * 64 + warp * 16 + (lane >> 2);
#pragma unroll
            for (int j = 0; j < 16; j++) {
                uint32_t a = sQ + (j >> 3) * 16384 + r * 128 + (((j & 7) ^ (r & 7)) << 4) + (lane & 3) * 4;
                st_shared_u32(a, pack_bf16(o[j * 4 + 0] * i0, o[j * 4 + 1] * i0));
                st_shared_u32(a + 1024, pack_bf16(o[j * 4 + 2] * i1, o[j * 4 + 3] * i1));
            }
            named_sync(3 + cw, 128);
#pragma unroll
            for (int i = 0; i < 8; i++) {
                int idx = i * 128 + tid;
                int rr = cw * 64 + (idx >> 4), ch = idx & 15;
                uint32_t a = sQ + (ch >> 3) * 16384 + rr * 128 + (((ch & 7) ^ (rr & 7)) << 4);
                uint4 v = ld_shared_v4(a);
                *reinterpret_cast<uint4*>(g_o + (size_t)(qt * 128 + rr) * HD + head * DH + ch * 8) = v;
            }
        }
    }
}

constexpr int F_STAGES = 8;
constexpr int F_SMEM = F_STAGES * G_STAGE_BYTES + 1024 + 256;
__global__ void __launch_bounds__(256, 1)
final_kernel(const __grid_constant__ CUtensorMap mapO, const __grid_constant__ CUtensorMap mapWo,
             const bf16* __restrict__ x, const bf16* __restrict__ gg, bf16* __restrict__ out) {
    extern __shared__ uint8_t smem_raw[];
    uint32_t sbase = (smem_u32(smem_raw) + 1023) & ~1023u;
    uint32_t bar_full = sbase + F_STAGES * G_STAGE_BYTES;
    uint32_t bar_empty = bar_full + 8 * F_STAGES;
    int wg = threadIdx.x >> 7;
    int tid = threadIdx.x & 127;
    int m0 = blockIdx.y * 64, n0 = blockIdx.x * 128;
    constexpr int NK1 = HD / 64;

    if (threadIdx.x == 0) {
        for (int i = 0; i < F_STAGES; i++) { mbar_init(bar_full + 8 * i, 1); mbar_init(bar_empty + 8 * i, 4); }
        fence_barrier_init();
    }
    __syncthreads();

    if (wg == 0) {
        if (tid == 0) {
            for (int it = 0; it < NK1; it++) {
                int s = it % F_STAGES;
                uint32_t ph = (it / F_STAGES) & 1;
                mbar_wait(bar_empty + 8 * s, ph ^ 1);
                mbar_expect_tx(bar_full + 8 * s, G_STAGE_BYTES);
                uint32_t a = sbase + s * G_STAGE_BYTES;
                int k = it * 64;
                tma_load_2d(a, &mapO, bar_full + 8 * s, k, m0);
                tma_load_2d(a + 8192, &mapWo, bar_full + 8 * s, n0, k);
                tma_load_2d(a + 8192 + 8192, &mapWo, bar_full + 8 * s, n0 + 64, k);
            }
        }
    } else {
        float acc[64];
        int warp = tid >> 5, lane = tid & 31;
        int r = warp * 16 + (lane >> 2);
        uint32_t xv[32], gv[32];
#pragma unroll
        for (int j = 0; j < 16; j++) {
            int c = n0 + j * 8 + (lane & 3) * 2;
            xv[j * 2] = *reinterpret_cast<const uint32_t*>(x + (size_t)(m0 + r) * DM + c);
            xv[j * 2 + 1] = *reinterpret_cast<const uint32_t*>(x + (size_t)(m0 + r + 8) * DM + c);
            gv[j * 2] = *reinterpret_cast<const uint32_t*>(gg + (size_t)(m0 + r) * DM + c);
            gv[j * 2 + 1] = *reinterpret_cast<const uint32_t*>(gg + (size_t)(m0 + r + 8) * DM + c);
        }
        for (int it = 0; it < NK1; it++) {
            int s = it % F_STAGES;
            uint32_t ph = (it / F_STAGES) & 1;
            mbar_wait(bar_full + 8 * s, ph);
            uint32_t a = sbase + s * G_STAGE_BYTES;
            uint32_t b = a + 8192;
            wgmma_fence();
#pragma unroll
            for (int kk = 0; kk < 4; kk++)
                wgmma_m64n128k16_ss<0, 1>(acc, make_desc(a + kk * 32, 16, 1024), make_desc(b + kk * 2048, 8192, 1024), (it | kk) != 0);
            wgmma_commit();
            wgmma_wait<1>();
            if (it > 0 && lane == 0) mbar_arrive(bar_empty + 8 * ((it - 1) % F_STAGES));
        }
        wgmma_wait<0>();
#pragma unroll
        for (int j = 0; j < 16; j++) {
            uint32_t a = sbase + r * 256 + ((j ^ (r & 7)) << 4) + (lane & 3) * 4;
#pragma unroll
            for (int h = 0; h < 2; h++) {
                float2 xf = __bfloat1622float2(*reinterpret_cast<const __nv_bfloat162*>(&xv[j * 2 + h]));
                float2 gf = __bfloat1622float2(*reinterpret_cast<const __nv_bfloat162*>(&gv[j * 2 + h]));
                st_shared_u32(a + h * 2048, pack_bf16(xf.x + acc[j * 4 + h * 2 + 0] * gf.x, xf.y + acc[j * 4 + h * 2 + 1] * gf.y));
            }
        }
        named_sync(1, 128);
#pragma unroll
        for (int i = 0; i < 8; i++) {
            int idx = i * 128 + tid;
            int rr = idx >> 4, ch = idx & 15;
            uint4 v = ld_shared_v4(sbase + rr * 256 + ((ch ^ (rr & 7)) << 4));
            *reinterpret_cast<uint4*>(out + (size_t)(m0 + rr) * DM + n0 + ch * 8) = v;
        }
    }
}

typedef CUresult (*EncodeFn)(CUtensorMap*, CUtensorMapDataType, cuuint32_t, void*, const cuuint64_t*, const cuuint64_t*,
                             const cuuint32_t*, const cuuint32_t*, CUtensorMapInterleave, CUtensorMapSwizzle,
                             CUtensorMapL2promotion, CUtensorMapFloatOOBfill);

static void make_map(EncodeFn fn, CUtensorMap* m, const void* ptr, uint64_t inner, uint64_t outer,
                     uint32_t box_inner, uint32_t box_outer) {
    cuuint64_t dims[2] = {inner, outer};
    cuuint64_t strides[1] = {inner * 2};
    cuuint32_t box[2] = {box_inner, box_outer};
    cuuint32_t es[2] = {1, 1};
    fn(m, CU_TENSOR_MAP_DATA_TYPE_BFLOAT16, 2, const_cast<void*>(ptr), dims, strides, box, es,
       CU_TENSOR_MAP_INTERLEAVE_NONE, CU_TENSOR_MAP_SWIZZLE_128B, CU_TENSOR_MAP_L2_PROMOTION_L2_256B,
       CU_TENSOR_MAP_FLOAT_OOB_FILL_NONE);
}

extern "C" void kernel_launch(void* const* d_in, const int* in_sizes, int n_in, void* d_out, int out_size) {
    const bf16* x  = (const bf16*)d_in[0];
    const bf16* kc = (const bf16*)d_in[1];
    const bf16* vc = (const bf16*)d_in[2];
    const bf16* wq = (const bf16*)d_in[3];
    const bf16* wo = (const bf16*)d_in[4];
    const bf16* w1 = (const bf16*)d_in[6];
    const bf16* b1 = (const bf16*)d_in[7];
    const bf16* w2 = (const bf16*)d_in[8];
    const bf16* b2 = (const bf16*)d_in[9];
    bf16* out = (bf16*)d_out;

    static bool inited = false;
    static CUtensorMap mXn, mY, mWq, mW1, mQ, mK, mV, mO, mWo, mH, mW2;
    static void *pq, *ph, *pg;
    static cudaStream_t s2;
    static cudaEvent_t evFork, evJoin;
    if (!inited) {
        EncodeFn fn = nullptr;
        cudaDriverEntryPointQueryResult qres;
        cudaGetDriverEntryPoint("cuTensorMapEncodeTiled", (void**)&fn, cudaEnableDefault, &qres);
        void *pxn, *py, *po;
        cudaGetSymbolAddress(&pxn, g_xn); cudaGetSymbolAddress(&py, g_y); cudaGetSymbolAddress(&pq, g_q);
        cudaGetSymbolAddress(&ph, g_h); cudaGetSymbolAddress(&po, g_o); cudaGetSymbolAddress(&pg, g_g);
        make_map(fn, &mXn, pxn, DM, SEQ, 64, 128);
        make_map(fn, &mY, py, DM, SEQ, 64, 64);
        make_map(fn, &mWq, wq, HD, DM, 64, 64);
        make_map(fn, &mW1, w1, FF, DM, 64, 64);
        make_map(fn, &mK, kc, DH, NH * SEQ, 64, 128);
        make_map(fn, &mV, vc, DH, NH * SEQ, 64, 128);
        make_map(fn, &mO, po, HD, SEQ, 64, 64);
        make_map(fn, &mWo, wo, DM, HD, 64, 64);
        make_map(fn, &mH, ph, FF, SEQ, 64, 64);
        make_map(fn, &mW2, w2, DM, FF, 64, 64);
        cudaFuncSetAttribute(mlp1_kernel<1, FF, DM>, cudaFuncAttributeMaxDynamicSharedMemorySize, M1_SMEM);
        cudaFuncSetAttribute(mlp1_kernel<2, DM, FF>, cudaFuncAttributeMaxDynamicSharedMemorySize, M1_SMEM);
        cudaFuncSetAttribute(final_kernel, cudaFuncAttributeMaxDynamicSharedMemorySize, F_SMEM);
        cudaFuncSetAttribute(attn_kernel, cudaFuncAttributeMaxDynamicSharedMemorySize, A_SMEM);
        cudaStreamCreateWithFlags(&s2, cudaStreamNonBlocking);
        cudaEventCreateWithFlags(&evFork, cudaEventDisableTiming);
        cudaEventCreateWithFlags(&evJoin, cudaEventDisableTiming);
        inited = true;
    }

    ln_kernel<<<SEQ / 8, 256>>>(x);
    cudaEventRecord(evFork, cudaStreamPerThread);
    attn_kernel<<<dim3(SEQ / 128, NH), 384, A_SMEM>>>(mXn, mWq, mK, mV);
    cudaStreamWaitEvent(s2, evFork, 0);
    mlp1_kernel<1, FF, DM><<<dim3((FF + 127) / 128, SEQ / 64), 256, M1_SMEM, s2>>>(mY, mW1, (bf16*)ph, b1);
    mlp1_kernel<2, DM, FF><<<dim3(DM / 128, SEQ / 64), 256, M1_SMEM, s2>>>(mH, mW2, (bf16*)pg, b2);
    cudaEventRecord(evJoin, s2);
    cudaStreamWaitEvent(cudaStreamPerThread, evJoin, 0);
    final_kernel<<<dim3(DM / 128, SEQ / 64), 256, F_SMEM>>>(mO, mWo, x, (const bf16*)pg, out);
}
```

```cpp
#include <cuda_runtime.h>
#include <cuda_bf16.h>
#include <cuda.h>
#include <stdint.h>

typedef __nv_bfloat16 bf16;

constexpr int SEQ = 2048;
constexpr int DM  = 512;
constexpr int NH  = 32;
constexpr int DH  = 128;
constexpr int HD  = NH * DH;
constexpr int FF  = 1376;

__device__ bf16 g_xn[SEQ * DM];
__device__ bf16 g_y [SEQ * DM];
__device__ bf16 g_q [SEQ * HD];
__device__ bf16 g_h [SEQ * FF];
__device__ bf16 g_o [SEQ * HD];

__device__ __forceinline__ uint32_t smem_u32(const void* p) {
    return (uint32_t)__cvta_generic_to_shared(p);
}
__device__ __forceinline__ void mbar_init(uint32_t bar, uint32_t count) {
    asm volatile("mbarrier.init.shared::cta.b64 [%0], %1;" :: "r"(bar), "r"(count) : "memory");
}
__device__ __forceinline__ void mbar_arrive(uint32_t bar) {
    asm volatile("mbarrier.arrive.shared::cta.b64 _, [%0];" :: "r"(bar) : "memory");
}
__device__ __forceinline__ void mbar_expect_tx(uint32_t bar, uint32_t bytes) {
    asm volatile("mbarrier.arrive.expect_tx.shared::cta.b64 _, [%0], %1;" :: "r"(bar), "r"(bytes) : "memory");
}
__device__ __forceinline__ void mbar_wait(uint32_t bar, uint32_t parity) {
    asm volatile(
        "{\n"
        ".reg .pred p;\n"
        "LAB_WAIT:\n"
        "mbarrier.try_wait.parity.shared::cta.b64 p, [%0], %1;\n"
        "@p bra DONE;\n"
        "bra LAB_WAIT;\n"
        "DONE:\n"
        "}\n" :: "r"(bar), "r"(parity) : "memory");
}
__device__ __forceinline__ void tma_load_2d(uint32_t dst, const CUtensorMap* map, uint32_t bar, int c0, int c1) {
    asm volatile(
        "cp.async.bulk.tensor.2d.shared::cluster.global.mbarrier::complete_tx::bytes [%0], [%1, {%3, %4}], [%2];"
        :: "r"(dst), "l"((uint64_t)map), "r"(bar), "r"(c0), "r"(c1) : "memory");
}
__device__ __forceinline__ void wgmma_fence() { asm volatile("wgmma.fence.sync.aligned;" ::: "memory"); }
__device__ __forceinline__ void wgmma_commit() { asm volatile("wgmma.commit_group.sync.aligned;" ::: "memory"); }
template <int N> __device__ __forceinline__ void wgmma_wait() {
    asm volatile("wgmma.wait_group.sync.aligned %0;" :: "n"(N) : "memory");
}
template <int R> __device__ __forceinline__ void reg_alloc() {
    asm volatile("setmaxnreg.inc.sync.aligned.u32 %0;" :: "n"(R));
}
template <int R> __device__ __forceinline__ void reg_dealloc() {
    asm volatile("setmaxnreg.dec.sync.aligned.u32 %0;" :: "n"(R));
}
__device__ __forceinline__ void fence_barrier_init() {
    asm volatile("fence.mbarrier_init.release.cluster;" ::: "memory");
}
__device__ __forceinline__ void fence_proxy_async() {
    asm volatile("fence.proxy.async.shared::cta;" ::: "memory");
}

__device__ __forceinline__ void named_sync(int id, int n) {
    asm volatile("bar.sync %0, %1;" :: "r"(id), "r"(n) : "memory");
}
__device__ __forceinline__ void named_arrive(int id, int n) {
    asm volatile("bar.arrive %0, %1;" :: "r"(id), "r"(n) : "memory");
}
__device__ __forceinline__ float fast_exp2(float x) {
    float y;
    asm("ex2.approx.ftz.f32 %0, %1;" : "=f"(y) : "f"(x));
    return y;
}

__device__ __forceinline__ void st_shared_u32(uint32_t a, uint32_t v) {
    asm volatile("st.shared.u32 [%0], %1;" :: "r"(a), "r"(v) : "memory");
}
__device__ __forceinline__ uint4 ld_shared_v4(uint32_t a) {
    uint4 v;
    asm volatile("ld.shared.v4.u32 {%0,%1,%2,%3}, [%4];" : "=r"(v.x), "=r"(v.y), "=r"(v.z), "=r"(v.w) : "r"(a) : "memory");
    return v;
}

__device__ __forceinline__ void tma_load_2d_mc(uint32_t dst, const CUtensorMap* map, uint32_t bar, int c0, int c1, uint16_t mask) {
    asm volatile(
        "cp.async.bulk.tensor.2d.shared::cluster.global.mbarrier::complete_tx::bytes.multicast::cluster [%0], [%1, {%3, %4}], [%2], %5;"
        :: "r"(dst), "l"((uint64_t)map), "r"(bar), "r"(c0), "r"(c1), "h"(mask) : "memory");
}
__device__ __forceinline__ void mbar_arrive_cluster(uint32_t bar, uint32_t cta) {
    asm volatile(
        "{\n.reg .b32 ra;\n"
        "mapa.shared::cluster.u32 ra, %0, %1;\n"
        "mbarrier.arrive.release.cluster.shared::cluster.b64 _, [ra];\n}\n"
        :: "r"(bar), "r"(cta) : "memory");
}
__device__ __forceinline__ void cluster_sync_all() {
    asm volatile("barrier.cluster.arrive.release.aligned;\nbarrier.cluster.wait.acquire.aligned;" ::: "memory");
}
__device__ __forceinline__ uint32_t cluster_ctarank() {
    uint32_t r; asm volatile("mov.u32 %0, %%cluster_ctarank;" : "=r"(r)); return r;
}

__device__ __forceinline__ uint64_t make_desc(uint32_t addr, uint32_t lbo_bytes, uint32_t sbo_bytes) {
    uint64_t d = 0;
    d |= (uint64_t)((addr & 0x3FFFF) >> 4);
    d |= (uint64_t)((lbo_bytes & 0x3FFFF) >> 4) << 16;
    d |= (uint64_t)((sbo_bytes & 0x3FFFF) >> 4) << 32;
    d |= (uint64_t)1 << 62;
    return d;
}

template <int TA, int TB>
__device__ __forceinline__ void wgmma_m64n128k16_ss(float (&d)[64], uint64_t da, uint64_t db, int scale_d) {
    asm volatile(
        "{\n.reg .pred p;\nsetp.ne.b32 p, %66, 0;\n"
        "wgmma.mma_async.sync.aligned.m64n128k16.f32.bf16.bf16 "
        "{%0,%1,%2,%3,%4,%5,%6,%7,%8,%9,%10,%11,%12,%13,%14,%15,"
        "%16,%17,%18,%19,%20,%21,%22,%23,%24,%25,%26,%27,%28,%29,%30,%31,"
        "%32,%33,%34,%35,%36,%37,%38,%39,%40,%41,%42,%43,%44,%45,%46,%47,"
        "%48,%49,%50,%51,%52,%53,%54,%55,%56,%57,%58,%59,%60,%61,%62,%63},"
        " %64, %65, p, 1, 1, %67, %68;\n}\n"
        : "+f"(d[0]), "+f"(d[1]), "+f"(d[2]), "+f"(d[3]), "+f"(d[4]), "+f"(d[5]), "+f"(d[6]), "+f"(d[7]),
          "+f"(d[8]), "+f"(d[9]), "+f"(d[10]), "+f"(d[11]), "+f"(d[12]), "+f"(d[13]), "+f"(d[14]), "+f"(d[15]),
          "+f"(d[16]), "+f"(d[17]), "+f"(d[18]), "+f"(d[19]), "+f"(d[20]), "+f"(d[21]), "+f"(d[22]), "+f"(d[23]),
          "+f"(d[24]), "+f"(d[25]), "+f"(d[26]), "+f"(d[27]), "+f"(d[28]), "+f"(d[29]), "+f"(d[30]), "+f"(d[31]),
          "+f"(d[32]), "+f"(d[33]), "+f"(d[34]), "+f"(d[35]), "+f"(d[36]), "+f"(d[37]), "+f"(d[38]), "+f"(d[39]),
          "+f"(d[40]), "+f"(d[41]), "+f"(d[42]), "+f"(d[43]), "+f"(d[44]), "+f"(d[45]), "+f"(d[46]), "+f"(d[47]),
          "+f"(d[48]), "+f"(d[49]), "+f"(d[50]), "+f"(d[51]), "+f"(d[52]), "+f"(d[53]), "+f"(d[54]), "+f"(d[55]),
          "+f"(d[56]), "+f"(d[57]), "+f"(d[58]), "+f"(d[59]), "+f"(d[60]), "+f"(d[61]), "+f"(d[62]), "+f"(d[63])
        : "l"(da), "l"(db), "r"(scale_d), "n"(TA), "n"(TB));
}

template <int TB>
__device__ __forceinline__ void wgmma_m64n128k16_rs(float (&d)[64], uint32_t a0, uint32_t a1, uint32_t a2, uint32_t a3,
                                                    uint64_t db, int scale_d) {
    asm volatile(
        "{\n.reg .pred p;\nsetp.ne.b32 p, %69, 0;\n"
        "wgmma.mma_async.sync.aligned.m64n128k16.f32.bf16.bf16 "
        "{%0,%1,%2,%3,%4,%5,%6,%7,%8,%9,%10,%11,%12,%13,%14,%15,"
        "%16,%17,%18,%19,%20,%21,%22,%23,%24,%25,%26,%27,%28,%29,%30,%31,"
        "%32,%33,%34,%35,%36,%37,%38,%39,%40,%41,%42,%43,%44,%45,%46,%47,"
        "%48,%49,%50,%51,%52,%53,%54,%55,%56,%57,%58,%59,%60,%61,%62,%63},"
        " {%64,%65,%66,%67}, %68, p, 1, 1, %70;\n}\n"
        : "+f"(d[0]), "+f"(d[1]), "+f"(d[2]), "+f"(d[3]), "+f"(d[4]), "+f"(d[5]), "+f"(d[6]), "+f"(d[7]),
          "+f"(d[8]), "+f"(d[9]), "+f"(d[10]), "+f"(d[11]), "+f"(d[12]), "+f"(d[13]), "+f"(d[14]), "+f"(d[15]),
          "+f"(d[16]), "+f"(d[17]), "+f"(d[18]), "+f"(d[19]), "+f"(d[20]), "+f"(d[21]), "+f"(d[22]), "+f"(d[23]),
          "+f"(d[24]), "+f"(d[25]), "+f"(d[26]), "+f"(d[27]), "+f"(d[28]), "+f"(d[29]), "+f"(d[30]), "+f"(d[31]),
          "+f"(d[32]), "+f"(d[33]), "+f"(d[34]), "+f"(d[35]), "+f"(d[36]), "+f"(d[37]), "+f"(d[38]), "+f"(d[39]),
          "+f"(d[40]), "+f"(d[41]), "+f"(d[42]), "+f"(d[43]), "+f"(d[44]), "+f"(d[45]), "+f"(d[46]), "+f"(d[47]),
          "+f"(d[48]), "+f"(d[49]), "+f"(d[50]), "+f"(d[51]), "+f"(d[52]), "+f"(d[53]), "+f"(d[54]), "+f"(d[55]),
          "+f"(d[56]), "+f"(d[57]), "+f"(d[58]), "+f"(d[59]), "+f"(d[60]), "+f"(d[61]), "+f"(d[62]), "+f"(d[63])
        : "r"(a0), "r"(a1), "r"(a2), "r"(a3), "l"(db), "r"(scale_d), "n"(TB));
}

__device__ __forceinline__ uint32_t pack_bf16(float lo, float hi) {
    __nv_bfloat162 v = __floats2bfloat162_rn(lo, hi);
    return *reinterpret_cast<uint32_t*>(&v);
}

__global__ void __launch_bounds__(256) ln_kernel(const bf16* __restrict__ x) {
    int warp = threadIdx.x >> 5, lane = threadIdx.x & 31;
    int row = blockIdx.x * 8 + warp;
    const uint4* src = reinterpret_cast<const uint4*>(x + (size_t)row * DM);
    float v[16];
#pragma unroll
    for (int i = 0; i < 2; i++) {
        uint4 u = src[lane + i * 32];
        const __nv_bfloat162* h = reinterpret_cast<const __nv_bfloat162*>(&u);
#pragma unroll
        for (int j = 0; j < 4; j++) {
            float2 f = __bfloat1622float2(h[j]);
            v[i * 8 + j * 2] = f.x; v[i * 8 + j * 2 + 1] = f.y;
        }
    }
#pragma unroll
    for (int pass = 0; pass < 2; pass++) {
        float s = 0.f;
#pragma unroll
        for (int i = 0; i < 16; i++) s += v[i];
#pragma unroll
        for (int o = 16; o > 0; o >>= 1) s += __shfl_xor_sync(0xffffffffu, s, o);
        float mean = s * (1.f / DM);
        float q = 0.f;
#pragma unroll
        for (int i = 0; i < 16; i++) { float d = v[i] - mean; q += d * d; }
#pragma unroll
        for (int o = 16; o > 0; o >>= 1) q += __shfl_xor_sync(0xffffffffu, q, o);
        float rstd = 1.0f / sqrtf(q * (1.f / DM) + 1e-5f);
        bf16* dst = (pass == 0 ? g_xn : g_y) + (size_t)row * DM;
#pragma unroll
        for (int i = 0; i < 2; i++) {
            uint4 u;
            uint32_t* w = reinterpret_cast<uint32_t*>(&u);
#pragma unroll
            for (int j = 0; j < 4; j++) {
                __nv_bfloat162 h = __floats2bfloat162_rn((v[i * 8 + j * 2] - mean) * rstd, (v[i * 8 + j * 2 + 1] - mean) * rstd);
                w[j] = *reinterpret_cast<uint32_t*>(&h);
                float2 f = __bfloat1622float2(h);
                v[i * 8 + j * 2] = f.x; v[i * 8 + j * 2 + 1] = f.y;
            }
            reinterpret_cast<uint4*>(dst)[lane + i * 32] = u;
        }
    }
}

constexpr int G_STAGE_BYTES = 8192 + 16384;

__device__ __forceinline__ float gelu_tanh(float x) {
    float u = 0.7978845608028654f * (x + 0.044715f * x * x * x);
    float t = 1.f - __fdividef(2.f, 1.f + __expf(2.f * u));
    return 0.5f * x * (1.f + t);
}

constexpr int M1_STAGES = 4;
constexpr int M1_SMEM = M1_STAGES * G_STAGE_BYTES + 1024 + 256;
__global__ void __launch_bounds__(256, 2)
mlp1_kernel(const __grid_constant__ CUtensorMap mapA, const __grid_constant__ CUtensorMap mapB,
            bf16* __restrict__ C, const bf16* __restrict__ bias) {
    extern __shared__ uint8_t smem_raw[];
    uint32_t sbase = (smem_u32(smem_raw) + 1023) & ~1023u;
    uint32_t bar_full = sbase + M1_STAGES * G_STAGE_BYTES;
    uint32_t bar_empty = bar_full + 8 * M1_STAGES;
    int wg = threadIdx.x >> 7;
    int tid = threadIdx.x & 127;
    int m0 = blockIdx.y * 64, n0 = blockIdx.x * 128;
    constexpr int nk = DM / 64;

    if (threadIdx.x == 0) {
        for (int i = 0; i < M1_STAGES; i++) { mbar_init(bar_full + 8 * i, 1); mbar_init(bar_empty + 8 * i, 4); }
        fence_barrier_init();
    }
    __syncthreads();

    if (wg == 0) {
        if (tid == 0) {
            for (int it = 0; it < nk; it++) {
                int s = it % M1_STAGES;
                uint32_t ph = (it / M1_STAGES) & 1;
                mbar_wait(bar_empty + 8 * s, ph ^ 1);
                mbar_expect_tx(bar_full + 8 * s, G_STAGE_BYTES);
                uint32_t a = sbase + s * G_STAGE_BYTES;
                tma_load_2d(a, &mapA, bar_full + 8 * s, it * 64, m0);
                tma_load_2d(a + 8192, &mapB, bar_full + 8 * s, n0, it * 64);
                tma_load_2d(a + 8192 + 8192, &mapB, bar_full + 8 * s, n0 + 64, it * 64);
            }
        }
    } else {
        float acc[64];
        int warp = tid >> 5, lane = tid & 31;
        uint32_t bv[16];
#pragma unroll
        for (int j = 0; j < 16; j++) {
            int c = min(n0 + j * 8 + (lane & 3) * 2, FF - 2);
            bv[j] = *reinterpret_cast<const uint32_t*>(bias + c);
        }
        for (int it = 0; it < nk; it++) {
            int s = it % M1_STAGES;
            uint32_t ph = (it / M1_STAGES) & 1;
            mbar_wait(bar_full + 8 * s, ph);
            uint32_t a = sbase + s * G_STAGE_BYTES;
            uint32_t b = a + 8192;
            wgmma_fence();
#pragma unroll
            for (int kk = 0; kk < 4; kk++)
                wgmma_m64n128k16_ss<0, 1>(acc, make_desc(a + kk * 32, 16, 1024), make_desc(b + kk * 2048, 8192, 1024), (it | kk) != 0);
            wgmma_commit();
            wgmma_wait<1>();
            if (it > 0 && lane == 0) mbar_arrive(bar_empty + 8 * ((it - 1) % M1_STAGES));
        }
        wgmma_wait<0>();
        int r = warp * 16 + (lane >> 2);
#pragma unroll
        for (int j = 0; j < 16; j++) {
            float2 bf = __bfloat1622float2(*reinterpret_cast<const __nv_bfloat162*>(&bv[j]));
            float b0 = bf.x, b1 = bf.y;
            uint32_t a = sbase + r * 256 + ((j ^ (r & 7)) << 4) + (lane & 3) * 4;
            st_shared_u32(a, pack_bf16(gelu_tanh(acc[j * 4 + 0] + b0), gelu_tanh(acc[j * 4 + 1] + b1)));
            st_shared_u32(a + 2048, pack_bf16(gelu_tanh(acc[j * 4 + 2] + b0), gelu_tanh(acc[j * 4 + 3] + b1)));
        }
        named_sync(1, 128);
#pragma unroll
        for (int i = 0; i < 8; i++) {
            int idx = i * 128 + tid;
            int rr = idx >> 4, ch = idx & 15;
            uint4 v = ld_shared_v4(sbase + rr * 256 + ((ch ^ (rr & 7)) << 4));
            if (n0 + ch * 8 < FF)
                *reinterpret_cast<uint4*>(C + (size_t)(m0 + rr) * FF + n0 + ch * 8) = v;
        }
    }
}

constexpr int A_KV_STAGES = 2;
constexpr int A_TILE_BYTES = 128 * 128 * 2;
constexpr int A_SMEM = A_TILE_BYTES * (1 + 2 * A_KV_STAGES) + 1024 + 256;

__global__ void __launch_bounds__(384, 1)
attn_kernel(const __grid_constant__ CUtensorMap mapXn, const __grid_constant__ CUtensorMap mapWq,
            const __grid_constant__ CUtensorMap mapK, const __grid_constant__ CUtensorMap mapV) {
    extern __shared__ uint8_t smem_raw[];
    uint32_t sbase = (smem_u32(smem_raw) + 1023) & ~1023u;
    uint32_t sQ = sbase;
    uint32_t sK = sQ + A_TILE_BYTES;
    uint32_t sV = sK + A_KV_STAGES * A_TILE_BYTES;
    uint32_t bars = sV + A_KV_STAGES * A_TILE_BYTES;
    uint32_t bar_pf = bars, bar_pe = bars + 32;
    uint32_t bar_kf = bars + 64, bar_ke = bar_kf + 8 * A_KV_STAGES;
    uint32_t bar_vf = bar_ke + 8 * A_KV_STAGES, bar_ve = bar_vf + 8 * A_KV_STAGES;
    int wg = threadIdx.x >> 7;
    int tid = threadIdx.x & 127;
    int qt = blockIdx.x, head = blockIdx.y;
    constexpr int NT = SEQ / 128;

    if (threadIdx.x == 0) {
        for (int i = 0; i < 4; i++) { mbar_init(bar_pf + 8 * i, 1); mbar_init(bar_pe + 8 * i, 8); }
        for (int i = 0; i < A_KV_STAGES; i++) {
            mbar_init(bar_kf + 8 * i, 1); mbar_init(bar_ke + 8 * i, 8);
            mbar_init(bar_vf + 8 * i, 1); mbar_init(bar_ve + 8 * i, 8);
        }
        fence_barrier_init();
    }
    __syncthreads();

    if (wg == 0) {
        reg_dealloc<40>();
        if (tid == 0) {
            for (int i = 0; i < 8; i++) {
                int b = i & 3;
                uint32_t buf = sK + b * A_TILE_BYTES;
                mbar_wait(bar_pe + 8 * b, ((i >> 2) & 1) ^ 1);
                mbar_expect_tx(bar_pf + 8 * b, A_TILE_BYTES);
                tma_load_2d(buf, &mapXn, bar_pf + 8 * b, i * 64, qt * 128);
                tma_load_2d(buf + 16384, &mapWq, bar_pf + 8 * b, head * DH, i * 64);
                tma_load_2d(buf + 16384 + 8192, &mapWq, bar_pf + 8 * b, head * DH + 64, i * 64);
            }
            for (int it = 0; it < NT; it++) {
                int s = it % A_KV_STAGES;
                uint32_t ph = (it / A_KV_STAGES) & 1;
                int row = head * SEQ + it * 128;
                if (it < A_KV_STAGES) mbar_wait(bar_pe + 8 * s, 1);
                else mbar_wait(bar_ke + 8 * s, ph ^ 1);
                mbar_expect_tx(bar_kf + 8 * s, A_TILE_BYTES);
                tma_load_2d(sK + s * A_TILE_BYTES, &mapK, bar_kf + 8 * s, 0, row);
                tma_load_2d(sK + s * A_TILE_BYTES + 16384, &mapK, bar_kf + 8 * s, 64, row);
                if (it < A_KV_STAGES) mbar_wait(bar_pe + 8 * (A_KV_STAGES + s), 1);
                else mbar_wait(bar_ve + 8 * s, ph ^ 1);
                mbar_expect_tx(bar_vf + 8 * s, A_TILE_BYTES);
                tma_load_2d(sV + s * A_TILE_BYTES, &mapV, bar_vf + 8 * s, 0, row);
                tma_load_2d(sV + s * A_TILE_BYTES + 16384, &mapV, bar_vf + 8 * s, 64, row);
            }
        }
    } else {
        reg_alloc<232>();
        int cw = wg - 1;
        int warp = tid >> 5, lane = tid & 31;
        float o[64];
        for (int i = 0; i < 8; i++) {
            int b = i & 3;
            uint32_t buf = sK + b * A_TILE_BYTES;
            mbar_wait(bar_pf + 8 * b, (i >> 2) & 1);
            wgmma_fence();
#pragma unroll
            for (int kk = 0; kk < 4; kk++)
                wgmma_m64n128k16_ss<0, 1>(o, make_desc(buf + cw * 8192 + kk * 32, 16, 1024),
                                          make_desc(buf + 16384 + kk * 2048, 8192, 1024), (i | kk) != 0);
            wgmma_commit();
            wgmma_wait<0>();
            if (lane == 0) mbar_arrive(bar_pe + 8 * b);
        }
        {
            int r = cw * 64 + warp * 16 + (lane >> 2);
#pragma unroll
            for (int j = 0; j < 16; j++) {
                uint32_t a = sQ + (j >> 3) * 16384 + r * 128 + (((j & 7) ^ (r & 7)) << 4) + (lane & 3) * 4;
                st_shared_u32(a, pack_bf16(o[j * 4 + 0], o[j * 4 + 1]));
                st_shared_u32(a + 1024, pack_bf16(o[j * 4 + 2], o[j * 4 + 3]));
            }
            fence_proxy_async();
            named_sync(3 + cw, 128);
        }
#pragma unroll
        for (int i = 0; i < 64; i++) o[i] = 0.f;
        float m0 = -INFINITY, m1 = -INFINITY, l0 = 0.f, l1 = 0.f;
        const float sc = 0.08838834764831845f * 1.4426950408889634f;
        if (cw == 1) named_arrive(1, 256);
        uint32_t qa = sQ + cw * 8192;
        float sacc[64];
        uint32_t p[32];
        mbar_wait(bar_kf, 0);
        named_sync(1 + cw, 256);
        wgmma_fence();
#pragma unroll
        for (int kk = 0; kk < 8; kk++) {
            uint32_t off = (kk >> 2) * 16384 + (kk & 3) * 32;
            wgmma_m64n128k16_ss<0, 0>(sacc, make_desc(qa + off, 16, 1024), make_desc(sK + off, 16, 1024), kk != 0);
        }
        wgmma_commit();
        named_arrive(1 + (cw ^ 1), 256);
        wgmma_wait<0>();
        if (lane == 0) mbar_arrive(bar_ke);
        {
            float mx0 = -INFINITY, mx1 = -INFINITY;
#pragma unroll
            for (int j = 0; j < 16; j++) {
                mx0 = fmaxf(mx0, fmaxf(sacc[j * 4 + 0], sacc[j * 4 + 1]));
                mx1 = fmaxf(mx1, fmaxf(sacc[j * 4 + 2], sacc[j * 4 + 3]));
            }
            mx0 = fmaxf(mx0, __shfl_xor_sync(0xffffffffu, mx0, 1));
            mx0 = fmaxf(mx0, __shfl_xor_sync(0xffffffffu, mx0, 2));
            mx1 = fmaxf(mx1, __shfl_xor_sync(0xffffffffu, mx1, 1));
            mx1 = fmaxf(mx1, __shfl_xor_sync(0xffffffffu, mx1, 2));
            m0 = mx0; m1 = mx1;
            float ms0 = mx0 * sc, ms1 = mx1 * sc;
#pragma unroll
            for (int j = 0; j < 16; j++) {
                float p0 = fast_exp2(sacc[j * 4 + 0] * sc - ms0);
                float p1 = fast_exp2(sacc[j * 4 + 1] * sc - ms0);
                float p2 = fast_exp2(sacc[j * 4 + 2] * sc - ms1);
                float p3 = fast_exp2(sacc[j * 4 + 3] * sc - ms1);
                l0 += p0 + p1; l1 += p2 + p3;
                p[j * 2 + 0] = pack_bf16(p0, p1);
                p[j * 2 + 1] = pack_bf16(p2, p3);
            }
        }
        for (int it = 1; it < NT; it++) {
            int s = it % A_KV_STAGES;
            uint32_t ph = (it / A_KV_STAGES) & 1;
            int sp = (it - 1) % A_KV_STAGES;
            uint32_t php = ((it - 1) / A_KV_STAGES) & 1;
            mbar_wait(bar_kf + 8 * s, ph);
            named_sync(1 + cw, 256);
            uint32_t kb = sK + s * A_TILE_BYTES;
            wgmma_fence();
#pragma unroll
            for (int kk = 0; kk < 8; kk++) {
                uint32_t off = (kk >> 2) * 16384 + (kk & 3) * 32;
                wgmma_m64n128k16_ss<0, 0>(sacc, make_desc(qa + off, 16, 1024), make_desc(kb + off, 16, 1024), kk != 0);
            }
            wgmma_commit();
            mbar_wait(bar_vf + 8 * sp, php);
            uint32_t vb = sV + sp * A_TILE_BYTES;
#pragma unroll
            for (int kk = 0; kk < 8; kk++) {
                wgmma_m64n128k16_rs<1>(o, p[kk * 4 + 0], p[kk * 4 + 1], p[kk * 4 + 2], p[kk * 4 + 3],
                                       make_desc(vb + kk * 2048, 16384, 1024), 1);
            }
            wgmma_commit();
            named_arrive(1 + (cw ^ 1), 256);
            wgmma_wait<1>();
            if (lane == 0) mbar_arrive(bar_ke + 8 * s);
            float mx0 = m0, mx1 = m1;
#pragma unroll
            for (int j = 0; j < 16; j++) {
                mx0 = fmaxf(mx0, fmaxf(sacc[j * 4 + 0], sacc[j * 4 + 1]));
                mx1 = fmaxf(mx1, fmaxf(sacc[j * 4 + 2], sacc[j * 4 + 3]));
            }
            mx0 = fmaxf(mx0, __shfl_xor_sync(0xffffffffu, mx0, 1));
            mx0 = fmaxf(mx0, __shfl_xor_sync(0xffffffffu, mx0, 2));
            mx1 = fmaxf(mx1, __shfl_xor_sync(0xffffffffu, mx1, 1));
            mx1 = fmaxf(mx1, __shfl_xor_sync(0xffffffffu, mx1, 2));
            float c0 = fast_exp2((m0 - mx0) * sc), c1 = fast_exp2((m1 - mx1) * sc);
            m0 = mx0; m1 = mx1;
            float ms0 = mx0 * sc, ms1 = mx1 * sc;
            float rs0 = 0.f, rs1 = 0.f;
#pragma unroll
            for (int j = 0; j < 16; j++) {
                sacc[j * 4 + 0] = fast_exp2(sacc[j * 4 + 0] * sc - ms0);
                sacc[j * 4 + 1] = fast_exp2(sacc[j * 4 + 1] * sc - ms0);
                sacc[j * 4 + 2] = fast_exp2(sacc[j * 4 + 2] * sc - ms1);
                sacc[j * 4 + 3] = fast_exp2(sacc[j * 4 + 3] * sc - ms1);
                rs0 += sacc[j * 4 + 0] + sacc[j * 4 + 1]; rs1 += sacc[j * 4 + 2] + sacc[j * 4 + 3];
            }
            l0 = l0 * c0 + rs0; l1 = l1 * c1 + rs1;
            wgmma_wait<0>();
            if (lane == 0) mbar_arrive(bar_ve + 8 * sp);
#pragma unroll
            for (int j = 0; j < 16; j++) {
                o[j * 4 + 0] *= c0; o[j * 4 + 1] *= c0; o[j * 4 + 2] *= c1; o[j * 4 + 3] *= c1;
                p[j * 2 + 0] = pack_bf16(sacc[j * 4 + 0], sacc[j * 4 + 1]);
                p[j * 2 + 1] = pack_bf16(sacc[j * 4 + 2], sacc[j * 4 + 3]);
            }
        }
        {
            int sp = (NT - 1) % A_KV_STAGES;
            uint32_t php = ((NT - 1) / A_KV_STAGES) & 1;
            mbar_wait(bar_vf + 8 * sp, php);
            uint32_t vb = sV + sp * A_TILE_BYTES;
            wgmma_fence();
#pragma unroll
            for (int kk = 0; kk < 8; kk++) {
                wgmma_m64n128k16_rs<1>(o, p[kk * 4 + 0], p[kk * 4 + 1], p[kk * 4 + 2], p[kk * 4 + 3],
                                       make_desc(vb + kk * 2048, 16384, 1024), 1);
            }
            wgmma_commit();
            wgmma_wait<0>();
        }
        l0 += __shfl_xor_sync(0xffffffffu, l0, 1);
        l0 += __shfl_xor_sync(0xffffffffu, l0, 2);
        l1 += __shfl_xor_sync(0xffffffffu, l1, 1);
        l1 += __shfl_xor_sync(0xffffffffu, l1, 2);
        float i0 = 1.f / l0, i1 = 1.f / l1;
        {
            int r = cw * 64 + warp * 16 + (lane >> 2);
#pragma unroll
            for (int j = 0; j < 16; j++) {
                uint32_t a = sQ + (j >> 3) * 16384 + r * 128 + (((j & 7) ^ (r & 7)) << 4) + (lane & 3) * 4;
                st_shared_u32(a, pack_bf16(o[j * 4 + 0] * i0, o[j * 4 + 1] * i0));
                st_shared_u32(a + 1024, pack_bf16(o[j * 4 + 2] * i1, o[j * 4 + 3] * i1));
            }
            named_sync(3 + cw, 128);
#pragma unroll
            for (int i = 0; i < 8; i++) {
                int idx = i * 128 + tid;
                int rr = cw * 64 + (idx >> 4), ch = idx & 15;
                uint32_t a = sQ + (ch >> 3) * 16384 + rr * 128 + (((ch & 7) ^ (rr & 7)) << 4);
                uint4 v = ld_shared_v4(a);
                *reinterpret_cast<uint4*>(g_o + (size_t)(qt * 128 + rr) * HD + head * DH + ch * 8) = v;
            }
        }
    }
}

constexpr int F_STAGES = 8;
constexpr int F_SMEM = F_STAGES * G_STAGE_BYTES + 1024 + 256;
__global__ void __cluster_dims__(1, 4, 1) __launch_bounds__(256, 1)
final_kernel(const __grid_constant__ CUtensorMap mapO, const __grid_constant__ CUtensorMap mapWo,
             const __grid_constant__ CUtensorMap mapH, const __grid_constant__ CUtensorMap mapW2,
             const bf16* __restrict__ x, const bf16* __restrict__ b2, bf16* __restrict__ out) {
    extern __shared__ uint8_t smem_raw[];
    uint32_t sbase = (smem_u32(smem_raw) + 1023) & ~1023u;
    uint32_t bar_full = sbase + F_STAGES * G_STAGE_BYTES;
    uint32_t bar_empty = bar_full + 8 * F_STAGES;
    int wg = threadIdx.x >> 7;
    int tid = threadIdx.x & 127;
    int m0 = blockIdx.y * 64, n0 = blockIdx.x * 128;
    constexpr int NK1 = HD / 64;
    constexpr int NK2 = (FF + 63) / 64;

    if (threadIdx.x == 0) {
        for (int i = 0; i < F_STAGES; i++) { mbar_init(bar_full + 8 * i, 1); mbar_init(bar_empty + 8 * i, 16); }
        fence_barrier_init();
    }
    cluster_sync_all();
    uint32_t rank = cluster_ctarank();

    if (wg == 0) {
        if (tid == 0) {
            for (int it = 0; it < NK1 + NK2; it++) {
                int s = it % F_STAGES;
                uint32_t ph = (it / F_STAGES) & 1;
                mbar_wait(bar_empty + 8 * s, ph ^ 1);
                mbar_expect_tx(bar_full + 8 * s, G_STAGE_BYTES);
                uint32_t a = sbase + s * G_STAGE_BYTES;
                const CUtensorMap* pa = it < NK2 ? &mapH : &mapO;
                const CUtensorMap* pb = it < NK2 ? &mapW2 : &mapWo;
                int k = (it < NK2 ? it : it - NK2) * 64;
                tma_load_2d(a, pa, bar_full + 8 * s, k, m0);
                tma_load_2d_mc(a + 8192 + rank * 2048, pb, bar_full + 8 * s, n0, k + rank * 16, 15);
                tma_load_2d_mc(a + 16384 + rank * 2048, pb, bar_full + 8 * s, n0 + 64, k + rank * 16, 15);
            }
        }
    } else {
        float acc[64], acc2[64];
        int warp = tid >> 5, lane = tid & 31;
        int r = warp * 16 + (lane >> 2);
        uint32_t xv[32], bv[16];
#pragma unroll
        for (int j = 0; j < 16; j++) {
            int c = n0 + j * 8 + (lane & 3) * 2;
            bv[j] = *reinterpret_cast<const uint32_t*>(b2 + c);
            xv[j * 2] = *reinterpret_cast<const uint32_t*>(x + (size_t)(m0 + r) * DM + c);
            xv[j * 2 + 1] = *reinterpret_cast<const uint32_t*>(x + (size_t)(m0 + r + 8) * DM + c);
        }
        for (int it = 0; it < NK2; it++) {
            int s = it % F_STAGES;
            uint32_t ph = (it / F_STAGES) & 1;
            mbar_wait(bar_full + 8 * s, ph);
            uint32_t a = sbase + s * G_STAGE_BYTES;
            uint32_t b = a + 8192;
            wgmma_fence();
#pragma unroll
            for (int kk = 0; kk < 4; kk++)
                wgmma_m64n128k16_ss<0, 1>(acc2, make_desc(a + kk * 32, 16, 1024), make_desc(b + kk * 2048, 8192, 1024), (it | kk) != 0);
            wgmma_commit();
            wgmma_wait<1>();
            if (it > 0 && lane < 4) mbar_arrive_cluster(bar_empty + 8 * ((it - 1) % F_STAGES), lane);
        }
        for (int it = NK2; it < NK1 + NK2; it++) {
            int s = it % F_STAGES;
            uint32_t ph = (it / F_STAGES) & 1;
            mbar_wait(bar_full + 8 * s, ph);
            uint32_t a = sbase + s * G_STAGE_BYTES;
            uint32_t b = a + 8192;
            wgmma_fence();
#pragma unroll
            for (int kk = 0; kk < 4; kk++)
                wgmma_m64n128k16_ss<0, 1>(acc, make_desc(a + kk * 32, 16, 1024), make_desc(b + kk * 2048, 8192, 1024), ((it - NK2) | kk) != 0);
            wgmma_commit();
            wgmma_wait<1>();
            if (lane < 4) mbar_arrive_cluster(bar_empty + 8 * ((it - 1) % F_STAGES), lane);
        }
        wgmma_wait<0>();
#pragma unroll
        for (int j = 0; j < 16; j++) {
            float2 bf = __bfloat1622float2(*reinterpret_cast<const __nv_bfloat162*>(&bv[j]));
            uint32_t a = sbase + r * 256 + ((j ^ (r & 7)) << 4) + (lane & 3) * 4;
#pragma unroll
            for (int h = 0; h < 2; h++) {
                float2 xf = __bfloat1622float2(*reinterpret_cast<const __nv_bfloat162*>(&xv[j * 2 + h]));
                float g0 = acc2[j * 4 + h * 2 + 0] + bf.x, g1 = acc2[j * 4 + h * 2 + 1] + bf.y;
                g0 = __fdividef(g0, 1.f + __expf(-g0)); g1 = __fdividef(g1, 1.f + __expf(-g1));
                st_shared_u32(a + h * 2048, pack_bf16(xf.x + acc[j * 4 + h * 2 + 0] * g0, xf.y + acc[j * 4 + h * 2 + 1] * g1));
            }
        }
        named_sync(1, 128);
#pragma unroll
        for (int i = 0; i < 8; i++) {
            int idx = i * 128 + tid;
            int rr = idx >> 4, ch = idx & 15;
            uint4 v = ld_shared_v4(sbase + rr * 256 + ((ch ^ (rr & 7)) << 4));
            *reinterpret_cast<uint4*>(out + (size_t)(m0 + rr) * DM + n0 + ch * 8) = v;
        }
    }
    cluster_sync_all();
}

typedef CUresult (*EncodeFn)(CUtensorMap*, CUtensorMapDataType, cuuint32_t, void*, const cuuint64_t*, const cuuint64_t*,
                             const cuuint32_t*, const cuuint32_t*, CUtensorMapInterleave, CUtensorMapSwizzle,
                             CUtensorMapL2promotion, CUtensorMapFloatOOBfill);

static void make_map(EncodeFn fn, CUtensorMap* m, const void* ptr, uint64_t inner, uint64_t outer,
                     uint32_t box_inner, uint32_t box_outer) {
    cuuint64_t dims[2] = {inner, outer};
    cuuint64_t strides[1] = {inner * 2};
    cuuint32_t box[2] = {box_inner, box_outer};
    cuuint32_t es[2] = {1, 1};
    fn(m, CU_TENSOR_MAP_DATA_TYPE_BFLOAT16, 2, const_cast<void*>(ptr), dims, strides, box, es,
       CU_TENSOR_MAP_INTERLEAVE_NONE, CU_TENSOR_MAP_SWIZZLE_128B, CU_TENSOR_MAP_L2_PROMOTION_L2_256B,
       CU_TENSOR_MAP_FLOAT_OOB_FILL_NONE);
}

extern "C" void kernel_launch(void* const* d_in, const int* in_sizes, int n_in, void* d_out, int out_size) {
    const bf16* x  = (const bf16*)d_in[0];
    const bf16* kc = (const bf16*)d_in[1];
    const bf16* vc = (const bf16*)d_in[2];
    const bf16* wq = (const bf16*)d_in[3];
    const bf16* wo = (const bf16*)d_in[4];
    const bf16* w1 = (const bf16*)d_in[6];
    const bf16* b1 = (const bf16*)d_in[7];
    const bf16* w2 = (const bf16*)d_in[8];
    const bf16* b2 = (const bf16*)d_in[9];
    bf16* out = (bf16*)d_out;

    static bool inited = false;
    static CUtensorMap mXn, mY, mWq, mW1, mQ, mK, mV, mO, mWo, mH, mW2;
    static void *pq, *ph;
    static cudaStream_t s2;
    static cudaEvent_t evFork, evJoin;
    if (!inited) {
        EncodeFn fn = nullptr;
        cudaDriverEntryPointQueryResult qres;
        cudaGetDriverEntryPoint("cuTensorMapEncodeTiled", (void**)&fn, cudaEnableDefault, &qres);
        void *pxn, *py, *po;
        cudaGetSymbolAddress(&pxn, g_xn); cudaGetSymbolAddress(&py, g_y); cudaGetSymbolAddress(&pq, g_q);
        cudaGetSymbolAddress(&ph, g_h); cudaGetSymbolAddress(&po, g_o);
        make_map(fn, &mXn, pxn, DM, SEQ, 64, 128);
        make_map(fn, &mY, py, DM, SEQ, 64, 64);
        make_map(fn, &mWq, wq, HD, DM, 64, 64);
        make_map(fn, &mW1, w1, FF, DM, 64, 64);
        make_map(fn, &mK, kc, DH, NH * SEQ, 64, 128);
        make_map(fn, &mV, vc, DH, NH * SEQ, 64, 128);
        make_map(fn, &mO, po, HD, SEQ, 64, 64);
        make_map(fn, &mWo, wo, DM, HD, 64, 16);
        make_map(fn, &mH, ph, FF, SEQ, 64, 64);
        make_map(fn, &mW2, w2, DM, FF, 64, 16);
        cudaFuncSetAttribute(mlp1_kernel, cudaFuncAttributeMaxDynamicSharedMemorySize, M1_SMEM);
        cudaFuncSetAttribute(final_kernel, cudaFuncAttributeMaxDynamicSharedMemorySize, F_SMEM);
        cudaFuncSetAttribute(attn_kernel, cudaFuncAttributeMaxDynamicSharedMemorySize, A_SMEM);
        cudaStreamCreateWithFlags(&s2, cudaStreamNonBlocking);
        cudaEventCreateWithFlags(&evFork, cudaEventDisableTiming);
        cudaEventCreateWithFlags(&evJoin, cudaEventDisableTiming);
        inited = true;
    }

    ln_kernel<<<SEQ / 8, 256>>>(x);
    cudaEventRecord(evFork, cudaStreamPerThread);
    attn_kernel<<<dim3(SEQ / 128, NH), 384, A_SMEM>>>(mXn, mWq, mK, mV);
    cudaStreamWaitEvent(s2, evFork, 0);
    mlp1_kernel<<<dim3((FF + 127) / 128, SEQ / 64), 256, M1_SMEM, s2>>>(mY, mW1, (bf16*)ph, b1);
    cudaEventRecord(evJoin, s2);
    cudaStreamWaitEvent(cudaStreamPerThread, evJoin, 0);
    final_kernel<<<dim3(DM / 128, SEQ / 64), 256, F_SMEM>>>(mO, mWo, mH, mW2, x, b2, out);
}
```

```cpp
#include <cuda_runtime.h>
#include <cuda_bf16.h>
#include <cuda.h>
#include <stdint.h>

typedef __nv_bfloat16 bf16;

constexpr int SEQ = 2048;
constexpr int DM  = 512;
constexpr int NH  = 32;
constexpr int DH  = 128;
constexpr int HD  = NH * DH;
constexpr int FF  = 1376;

__device__ bf16 g_xn[SEQ * DM];
__device__ bf16 g_y [SEQ * DM];
__device__ bf16 g_q [SEQ * HD];
__device__ bf16 g_h [SEQ * FF];
__device__ bf16 g_o [SEQ * HD];

__device__ __forceinline__ uint32_t smem_u32(const void* p) {
    return (uint32_t)__cvta_generic_to_shared(p);
}
__device__ __forceinline__ void mbar_init(uint32_t bar, uint32_t count) {
    asm volatile("mbarrier.init.shared::cta.b64 [%0], %1;" :: "r"(bar), "r"(count) : "memory");
}
__device__ __forceinline__ void mbar_arrive(uint32_t bar) {
    asm volatile("mbarrier.arrive.shared::cta.b64 _, [%0];" :: "r"(bar) : "memory");
}
__device__ __forceinline__ void mbar_expect_tx(uint32_t bar, uint32_t bytes) {
    asm volatile("mbarrier.arrive.expect_tx.shared::cta.b64 _, [%0], %1;" :: "r"(bar), "r"(bytes) : "memory");
}
__device__ __forceinline__ void mbar_wait(uint32_t bar, uint32_t parity) {
    asm volatile(
        "{\n"
        ".reg .pred p;\n"
        "LAB_WAIT:\n"
        "mbarrier.try_wait.parity.shared::cta.b64 p, [%0], %1;\n"
        "@p bra DONE;\n"
        "bra LAB_WAIT;\n"
        "DONE:\n"
        "}\n" :: "r"(bar), "r"(parity) : "memory");
}
__device__ __forceinline__ void tma_load_2d(uint32_t dst, const CUtensorMap* map, uint32_t bar, int c0, int c1) {
    asm volatile(
        "cp.async.bulk.tensor.2d.shared::cluster.global.mbarrier::complete_tx::bytes [%0], [%1, {%3, %4}], [%2];"
        :: "r"(dst), "l"((uint64_t)map), "r"(bar), "r"(c0), "r"(c1) : "memory");
}
__device__ __forceinline__ void wgmma_fence() { asm volatile("wgmma.fence.sync.aligned;" ::: "memory"); }
__device__ __forceinline__ void wgmma_commit() { asm volatile("wgmma.commit_group.sync.aligned;" ::: "memory"); }
template <int N> __device__ __forceinline__ void wgmma_wait() {
    asm volatile("wgmma.wait_group.sync.aligned %0;" :: "n"(N) : "memory");
}
template <int R> __device__ __forceinline__ void reg_alloc() {
    asm volatile("setmaxnreg.inc.sync.aligned.u32 %0;" :: "n"(R));
}
template <int R> __device__ __forceinline__ void reg_dealloc() {
    asm volatile("setmaxnreg.dec.sync.aligned.u32 %0;" :: "n"(R));
}
__device__ __forceinline__ void fence_barrier_init() {
    asm volatile("fence.mbarrier_init.release.cluster;" ::: "memory");
}
__device__ __forceinline__ void fence_proxy_async() {
    asm volatile("fence.proxy.async.shared::cta;" ::: "memory");
}

__device__ __forceinline__ void named_sync(int id, int n) {
    asm volatile("bar.sync %0, %1;" :: "r"(id), "r"(n) : "memory");
}
__device__ __forceinline__ void named_arrive(int id, int n) {
    asm volatile("bar.arrive %0, %1;" :: "r"(id), "r"(n) : "memory");
}
__device__ __forceinline__ float fast_exp2(float x) {
    float y;
    asm("ex2.approx.ftz.f32 %0, %1;" : "=f"(y) : "f"(x));
    return y;
}

__device__ __forceinline__ void st_shared_u32(uint32_t a, uint32_t v) {
    asm volatile("st.shared.u32 [%0], %1;" :: "r"(a), "r"(v) : "memory");
}
__device__ __forceinline__ uint4 ld_shared_v4(uint32_t a) {
    uint4 v;
    asm volatile("ld.shared.v4.u32 {%0,%1,%2,%3}, [%4];" : "=r"(v.x), "=r"(v.y), "=r"(v.z), "=r"(v.w) : "r"(a) : "memory");
    return v;
}

__device__ __forceinline__ void tma_load_2d_mc(uint32_t dst, const CUtensorMap* map, uint32_t bar, int c0, int c1, uint16_t mask) {
    asm volatile(
        "cp.async.bulk.tensor.2d.shared::cluster.global.mbarrier::complete_tx::bytes.multicast::cluster [%0], [%1, {%3, %4}], [%2], %5;"
        :: "r"(dst), "l"((uint64_t)map), "r"(bar), "r"(c0), "r"(c1), "h"(mask) : "memory");
}
__device__ __forceinline__ void mbar_arrive_cluster(uint32_t bar, uint32_t cta) {
    asm volatile(
        "{\n.reg .b32 ra;\n"
        "mapa.shared::cluster.u32 ra, %0, %1;\n"
        "mbarrier.arrive.release.cluster.shared::cluster.b64 _, [ra];\n}\n"
        :: "r"(bar), "r"(cta) : "memory");
}
__device__ __forceinline__ void cluster_sync_all() {
    asm volatile("barrier.cluster.arrive.release.aligned;\nbarrier.cluster.wait.acquire.aligned;" ::: "memory");
}
__device__ __forceinline__ uint32_t cluster_ctarank() {
    uint32_t r; asm volatile("mov.u32 %0, %%cluster_ctarank;" : "=r"(r)); return r;
}

__device__ __forceinline__ uint64_t make_desc(uint32_t addr, uint32_t lbo_bytes, uint32_t sbo_bytes) {
    uint64_t d = 0;
    d |= (uint64_t)((addr & 0x3FFFF) >> 4);
    d |= (uint64_t)((lbo_bytes & 0x3FFFF) >> 4) << 16;
    d |= (uint64_t)((sbo_bytes & 0x3FFFF) >> 4) << 32;
    d |= (uint64_t)1 << 62;
    return d;
}

template <int TA, int TB>
__device__ __forceinline__ void wgmma_m64n128k16_ss(float (&d)[64], uint64_t da, uint64_t db, int scale_d) {
    asm volatile(
        "{\n.reg .pred p;\nsetp.ne.b32 p, %66, 0;\n"
        "wgmma.mma_async.sync.aligned.m64n128k16.f32.bf16.bf16 "
        "{%0,%1,%2,%3,%4,%5,%6,%7,%8,%9,%10,%11,%12,%13,%14,%15,"
        "%16,%17,%18,%19,%20,%21,%22,%23,%24,%25,%26,%27,%28,%29,%30,%31,"
        "%32,%33,%34,%35,%36,%37,%38,%39,%40,%41,%42,%43,%44,%45,%46,%47,"
        "%48,%49,%50,%51,%52,%53,%54,%55,%56,%57,%58,%59,%60,%61,%62,%63},"
        " %64, %65, p, 1, 1, %67, %68;\n}\n"
        : "+f"(d[0]), "+f"(d[1]), "+f"(d[2]), "+f"(d[3]), "+f"(d[4]), "+f"(d[5]), "+f"(d[6]), "+f"(d[7]),
          "+f"(d[8]), "+f"(d[9]), "+f"(d[10]), "+f"(d[11]), "+f"(d[12]), "+f"(d[13]), "+f"(d[14]), "+f"(d[15]),
          "+f"(d[16]), "+f"(d[17]), "+f"(d[18]), "+f"(d[19]), "+f"(d[20]), "+f"(d[21]), "+f"(d[22]), "+f"(d[23]),
          "+f"(d[24]), "+f"(d[25]), "+f"(d[26]), "+f"(d[27]), "+f"(d[28]), "+f"(d[29]), "+f"(d[30]), "+f"(d[31]),
          "+f"(d[32]), "+f"(d[33]), "+f"(d[34]), "+f"(d[35]), "+f"(d[36]), "+f"(d[37]), "+f"(d[38]), "+f"(d[39]),
          "+f"(d[40]), "+f"(d[41]), "+f"(d[42]), "+f"(d[43]), "+f"(d[44]), "+f"(d[45]), "+f"(d[46]), "+f"(d[47]),
          "+f"(d[48]), "+f"(d[49]), "+f"(d[50]), "+f"(d[51]), "+f"(d[52]), "+f"(d[53]), "+f"(d[54]), "+f"(d[55]),
          "+f"(d[56]), "+f"(d[57]), "+f"(d[58]), "+f"(d[59]), "+f"(d[60]), "+f"(d[61]), "+f"(d[62]), "+f"(d[63])
        : "l"(da), "l"(db), "r"(scale_d), "n"(TA), "n"(TB));
}

template <int TB>
__device__ __forceinline__ void wgmma_m64n128k16_rs(float (&d)[64], uint32_t a0, uint32_t a1, uint32_t a2, uint32_t a3,
                                                    uint64_t db, int scale_d) {
    asm volatile(
        "{\n.reg .pred p;\nsetp.ne.b32 p, %69, 0;\n"
        "wgmma.mma_async.sync.aligned.m64n128k16.f32.bf16.bf16 "
        "{%0,%1,%2,%3,%4,%5,%6,%7,%8,%9,%10,%11,%12,%13,%14,%15,"
        "%16,%17,%18,%19,%20,%21,%22,%23,%24,%25,%26,%27,%28,%29,%30,%31,"
        "%32,%33,%34,%35,%36,%37,%38,%39,%40,%41,%42,%43,%44,%45,%46,%47,"
        "%48,%49,%50,%51,%52,%53,%54,%55,%56,%57,%58,%59,%60,%61,%62,%63},"
        " {%64,%65,%66,%67}, %68, p, 1, 1, %70;\n}\n"
        : "+f"(d[0]), "+f"(d[1]), "+f"(d[2]), "+f"(d[3]), "+f"(d[4]), "+f"(d[5]), "+f"(d[6]), "+f"(d[7]),
          "+f"(d[8]), "+f"(d[9]), "+f"(d[10]), "+f"(d[11]), "+f"(d[12]), "+f"(d[13]), "+f"(d[14]), "+f"(d[15]),
          "+f"(d[16]), "+f"(d[17]), "+f"(d[18]), "+f"(d[19]), "+f"(d[20]), "+f"(d[21]), "+f"(d[22]), "+f"(d[23]),
          "+f"(d[24]), "+f"(d[25]), "+f"(d[26]), "+f"(d[27]), "+f"(d[28]), "+f"(d[29]), "+f"(d[30]), "+f"(d[31]),
          "+f"(d[32]), "+f"(d[33]), "+f"(d[34]), "+f"(d[35]), "+f"(d[36]), "+f"(d[37]), "+f"(d[38]), "+f"(d[39]),
          "+f"(d[40]), "+f"(d[41]), "+f"(d[42]), "+f"(d[43]), "+f"(d[44]), "+f"(d[45]), "+f"(d[46]), "+f"(d[47]),
          "+f"(d[48]), "+f"(d[49]), "+f"(d[50]), "+f"(d[51]), "+f"(d[52]), "+f"(d[53]), "+f"(d[54]), "+f"(d[55]),
          "+f"(d[56]), "+f"(d[57]), "+f"(d[58]), "+f"(d[59]), "+f"(d[60]), "+f"(d[61]), "+f"(d[62]), "+f"(d[63])
        : "r"(a0), "r"(a1), "r"(a2), "r"(a3), "l"(db), "r"(scale_d), "n"(TB));
}

__device__ __forceinline__ uint32_t pack_bf16(float lo, float hi) {
    __nv_bfloat162 v = __floats2bfloat162_rn(lo, hi);
    return *reinterpret_cast<uint32_t*>(&v);
}

__global__ void __launch_bounds__(256) ln_kernel(const bf16* __restrict__ x) {
    int warp = threadIdx.x >> 5, lane = threadIdx.x & 31;
    int row = blockIdx.x * 8 + warp;
    const uint4* src = reinterpret_cast<const uint4*>(x + (size_t)row * DM);
    float v[16];
#pragma unroll
    for (int i = 0; i < 2; i++) {
        uint4 u = src[lane + i * 32];
        const __nv_bfloat162* h = reinterpret_cast<const __nv_bfloat162*>(&u);
#pragma unroll
        for (int j = 0; j < 4; j++) {
            float2 f = __bfloat1622float2(h[j]);
            v[i * 8 + j * 2] = f.x; v[i * 8 + j * 2 + 1] = f.y;
        }
    }
#pragma unroll
    for (int pass = 0; pass < 2; pass++) {
        float s = 0.f;
#pragma unroll
        for (int i = 0; i < 16; i++) s += v[i];
#pragma unroll
        for (int o = 16; o > 0; o >>= 1) s += __shfl_xor_sync(0xffffffffu, s, o);
        float mean = s * (1.f / DM);
        float q = 0.f;
#pragma unroll
        for (int i = 0; i < 16; i++) { float d = v[i] - mean; q += d * d; }
#pragma unroll
        for (int o = 16; o > 0; o >>= 1) q += __shfl_xor_sync(0xffffffffu, q, o);
        float rstd = 1.0f / sqrtf(q * (1.f / DM) + 1e-5f);
        bf16* dst = (pass == 0 ? g_xn : g_y) + (size_t)row * DM;
#pragma unroll
        for (int i = 0; i < 2; i++) {
            uint4 u;
            uint32_t* w = reinterpret_cast<uint32_t*>(&u);
#pragma unroll
            for (int j = 0; j < 4; j++) {
                __nv_bfloat162 h = __floats2bfloat162_rn((v[i * 8 + j * 2] - mean) * rstd, (v[i * 8 + j * 2 + 1] - mean) * rstd);
                w[j] = *reinterpret_cast<uint32_t*>(&h);
                float2 f = __bfloat1622float2(h);
                v[i * 8 + j * 2] = f.x; v[i * 8 + j * 2 + 1] = f.y;
            }
            reinterpret_cast<uint4*>(dst)[lane + i * 32] = u;
        }
    }
}

constexpr int G_STAGE_BYTES = 8192 + 16384;

__device__ __forceinline__ float gelu_tanh(float x) {
    float u = 0.7978845608028654f * (x + 0.044715f * x * x * x);
    float t = 1.f - __fdividef(2.f, 1.f + __expf(2.f * u));
    return 0.5f * x * (1.f + t);
}

constexpr int M1_STAGES = 4;
constexpr int M1_SMEM = M1_STAGES * G_STAGE_BYTES + 1024 + 256;
__global__ void __launch_bounds__(256, 2)
mlp1_kernel(const __grid_constant__ CUtensorMap mapA, const __grid_constant__ CUtensorMap mapB,
            bf16* __restrict__ C, const bf16* __restrict__ bias) {
    extern __shared__ uint8_t smem_raw[];
    uint32_t sbase = (smem_u32(smem_raw) + 1023) & ~1023u;
    uint32_t bar_full = sbase + M1_STAGES * G_STAGE_BYTES;
    uint32_t bar_empty = bar_full + 8 * M1_STAGES;
    int wg = threadIdx.x >> 7;
    int tid = threadIdx.x & 127;
    int m0 = blockIdx.y * 64, n0 = blockIdx.x * 128;
    constexpr int nk = DM / 64;

    if (threadIdx.x == 0) {
        for (int i = 0; i < M1_STAGES; i++) { mbar_init(bar_full + 8 * i, 1); mbar_init(bar_empty + 8 * i, 4); }
        fence_barrier_init();
    }
    __syncthreads();

    if (wg == 0) {
        if (tid == 0) {
            for (int it = 0; it < nk; it++) {
                int s = it % M1_STAGES;
                uint32_t ph = (it / M1_STAGES) & 1;
                mbar_wait(bar_empty + 8 * s, ph ^ 1);
                mbar_expect_tx(bar_full + 8 * s, G_STAGE_BYTES);
                uint32_t a = sbase + s * G_STAGE_BYTES;
                tma_load_2d(a, &mapA, bar_full + 8 * s, it * 64, m0);
                tma_load_2d(a + 8192, &mapB, bar_full + 8 * s, n0, it * 64);
                tma_load_2d(a + 8192 + 8192, &mapB, bar_full + 8 * s, n0 + 64, it * 64);
            }
        }
    } else {
        float acc[64];
        int warp = tid >> 5, lane = tid & 31;
        uint32_t bv[16];
#pragma unroll
        for (int j = 0; j < 16; j++) {
            int c = min(n0 + j * 8 + (lane & 3) * 2, FF - 2);
            bv[j] = *reinterpret_cast<const uint32_t*>(bias + c);
        }
        for (int it = 0; it < nk; it++) {
            int s = it % M1_STAGES;
            uint32_t ph = (it / M1_STAGES) & 1;
            mbar_wait(bar_full + 8 * s, ph);
            uint32_t a = sbase + s * G_STAGE_BYTES;
            uint32_t b = a + 8192;
            wgmma_fence();
#pragma unroll
            for (int kk = 0; kk < 4; kk++)
                wgmma_m64n128k16_ss<0, 1>(acc, make_desc(a + kk * 32, 16, 1024), make_desc(b + kk * 2048, 8192, 1024), (it | kk) != 0);
            wgmma_commit();
            wgmma_wait<1>();
            if (it > 0 && lane == 0) mbar_arrive(bar_empty + 8 * ((it - 1) % M1_STAGES));
        }
        wgmma_wait<0>();
        int r = warp * 16 + (lane >> 2);
#pragma unroll
        for (int j = 0; j < 16; j++) {
            float2 bf = __bfloat1622float2(*reinterpret_cast<const __nv_bfloat162*>(&bv[j]));
            float b0 = bf.x, b1 = bf.y;
            uint32_t a = sbase + r * 256 + ((j ^ (r & 7)) << 4) + (lane & 3) * 4;
            st_shared_u32(a, pack_bf16(gelu_tanh(acc[j * 4 + 0] + b0), gelu_tanh(acc[j * 4 + 1] + b1)));
            st_shared_u32(a + 2048, pack_bf16(gelu_tanh(acc[j * 4 + 2] + b0), gelu_tanh(acc[j * 4 + 3] + b1)));
        }
        named_sync(1, 128);
#pragma unroll
        for (int i = 0; i < 8; i++) {
            int idx = i * 128 + tid;
            int rr = idx >> 4, ch = idx & 15;
            uint4 v = ld_shared_v4(sbase + rr * 256 + ((ch ^ (rr & 7)) << 4));
            if (n0 + ch * 8 < FF)
                *reinterpret_cast<uint4*>(C + (size_t)(m0 + rr) * FF + n0 + ch * 8) = v;
        }
    }
}

constexpr int A_KV_STAGES = 2;
constexpr int A_TILE_BYTES = 128 * 128 * 2;
constexpr int A_SMEM = A_TILE_BYTES * (1 + 2 * A_KV_STAGES) + 1024 + 256;

__global__ void __launch_bounds__(384, 1)
attn_kernel(const __grid_constant__ CUtensorMap mapXn, const __grid_constant__ CUtensorMap mapWq,
            const __grid_constant__ CUtensorMap mapK, const __grid_constant__ CUtensorMap mapV) {
    extern __shared__ uint8_t smem_raw[];
    uint32_t sbase = (smem_u32(smem_raw) + 1023) & ~1023u;
    uint32_t sQ = sbase;
    uint32_t sK = sQ + A_TILE_BYTES;
    uint32_t sV = sK + A_KV_STAGES * A_TILE_BYTES;
    uint32_t bars = sV + A_KV_STAGES * A_TILE_BYTES;
    uint32_t bar_pf = bars, bar_pe = bars + 32;
    uint32_t bar_kf = bars + 64, bar_ke = bar_kf + 8 * A_KV_STAGES;
    uint32_t bar_vf = bar_ke + 8 * A_KV_STAGES, bar_ve = bar_vf + 8 * A_KV_STAGES;
    int wg = threadIdx.x >> 7;
    int tid = threadIdx.x & 127;
    int qt = blockIdx.x, head = blockIdx.y;
    constexpr int NT = SEQ / 128;

    if (threadIdx.x == 0) {
        for (int i = 0; i < 4; i++) { mbar_init(bar_pf + 8 * i, 1); mbar_init(bar_pe + 8 * i, 8); }
        for (int i = 0; i < A_KV_STAGES; i++) {
            mbar_init(bar_kf + 8 * i, 1); mbar_init(bar_ke + 8 * i, 8);
            mbar_init(bar_vf + 8 * i, 1); mbar_init(bar_ve + 8 * i, 8);
        }
        fence_barrier_init();
    }
    __syncthreads();

    if (wg == 0) {
        reg_dealloc<40>();
        if (tid == 0) {
            for (int i = 0; i < 8; i++) {
                int b = i & 3;
                uint32_t buf = sK + b * A_TILE_BYTES;
                mbar_wait(bar_pe + 8 * b, ((i >> 2) & 1) ^ 1);
                mbar_expect_tx(bar_pf + 8 * b, A_TILE_BYTES);
                tma_load_2d(buf, &mapXn, bar_pf + 8 * b, i * 64, qt * 128);
                tma_load_2d(buf + 16384, &mapWq, bar_pf + 8 * b, head * DH, i * 64);
                tma_load_2d(buf + 16384 + 8192, &mapWq, bar_pf + 8 * b, head * DH + 64, i * 64);
            }
            for (int it = 0; it < NT; it++) {
                int s = it % A_KV_STAGES;
                uint32_t ph = (it / A_KV_STAGES) & 1;
                int row = head * SEQ + it * 128;
                if (it < A_KV_STAGES) mbar_wait(bar_pe + 8 * s, 1);
                else mbar_wait(bar_ke + 8 * s, ph ^ 1);
                mbar_expect_tx(bar_kf + 8 * s, A_TILE_BYTES);
                tma_load_2d(sK + s * A_TILE_BYTES, &mapK, bar_kf + 8 * s, 0, row);
                tma_load_2d(sK + s * A_TILE_BYTES + 16384, &mapK, bar_kf + 8 * s, 64, row);
                if (it < A_KV_STAGES) mbar_wait(bar_pe + 8 * (A_KV_STAGES + s), 1);
                else mbar_wait(bar_ve + 8 * s, ph ^ 1);
                mbar_expect_tx(bar_vf + 8 * s, A_TILE_BYTES);
                tma_load_2d(sV + s * A_TILE_BYTES, &mapV, bar_vf + 8 * s, 0, row);
                tma_load_2d(sV + s * A_TILE_BYTES + 16384, &mapV, bar_vf + 8 * s, 64, row);
            }
        }
    } else {
        reg_alloc<232>();
        int cw = wg - 1;
        int warp = tid >> 5, lane = tid & 31;
        float o[64];
        for (int i = 0; i < 8; i++) {
            int b = i & 3;
            uint32_t buf = sK + b * A_TILE_BYTES;
            mbar_wait(bar_pf + 8 * b, (i >> 2) & 1);
            wgmma_fence();
#pragma unroll
            for (int kk = 0; kk < 4; kk++)
                wgmma_m64n128k16_ss<0, 1>(o, make_desc(buf + cw * 8192 + kk * 32, 16, 1024),
                                          make_desc(buf + 16384 + kk * 2048, 8192, 1024), (i | kk) != 0);
            wgmma_commit();
            wgmma_wait<0>();
            if (lane == 0) mbar_arrive(bar_pe + 8 * b);
        }
        {
            int r = cw * 64 + warp * 16 + (lane >> 2);
#pragma unroll
            for (int j = 0; j < 16; j++) {
                uint32_t a = sQ + (j >> 3) * 16384 + r * 128 + (((j & 7) ^ (r & 7)) << 4) + (lane & 3) * 4;
                st_shared_u32(a, pack_bf16(o[j * 4 + 0], o[j * 4 + 1]));
                st_shared_u32(a + 1024, pack_bf16(o[j * 4 + 2], o[j * 4 + 3]));
            }
            fence_proxy_async();
            named_sync(3 + cw, 128);
        }
#pragma unroll
        for (int i = 0; i < 64; i++) o[i] = 0.f;
        float m0 = -INFINITY, m1 = -INFINITY, l0 = 0.f, l1 = 0.f;
        const float sc = 0.08838834764831845f * 1.4426950408889634f;
        if (cw == 1) named_arrive(1, 256);
        uint32_t qa = sQ + cw * 8192;
        float sacc[64];
        uint32_t p[32];
        mbar_wait(bar_kf, 0);
        named_sync(1 + cw, 256);
        wgmma_fence();
#pragma unroll
        for (int kk = 0; kk < 8; kk++) {
            uint32_t off = (kk >> 2) * 16384 + (kk & 3) * 32;
            wgmma_m64n128k16_ss<0, 0>(sacc, make_desc(qa + off, 16, 1024), make_desc(sK + off, 16, 1024), kk != 0);
        }
        wgmma_commit();
        named_arrive(1 + (cw ^ 1), 256);
        wgmma_wait<0>();
        if (lane == 0) mbar_arrive(bar_ke);
        {
            float mx0 = -INFINITY, mx1 = -INFINITY;
#pragma unroll
            for (int j = 0; j < 16; j++) {
                mx0 = fmaxf(mx0, fmaxf(sacc[j * 4 + 0], sacc[j * 4 + 1]));
                mx1 = fmaxf(mx1, fmaxf(sacc[j * 4 + 2], sacc[j * 4 + 3]));
            }
            mx0 = fmaxf(mx0, __shfl_xor_sync(0xffffffffu, mx0, 1));
            mx0 = fmaxf(mx0, __shfl_xor_sync(0xffffffffu, mx0, 2));
            mx1 = fmaxf(mx1, __shfl_xor_sync(0xffffffffu, mx1, 1));
            mx1 = fmaxf(mx1, __shfl_xor_sync(0xffffffffu, mx1, 2));
            m0 = mx0; m1 = mx1;
            float ms0 = mx0 * sc, ms1 = mx1 * sc;
#pragma unroll
            for (int j = 0; j < 16; j++) {
                float p0 = fast_exp2(sacc[j * 4 + 0] * sc - ms0);
                float p1 = fast_exp2(sacc[j * 4 + 1] * sc - ms0);
                float p2 = fast_exp2(sacc[j * 4 + 2] * sc - ms1);
                float p3 = fast_exp2(sacc[j * 4 + 3] * sc - ms1);
                l0 += p0 + p1; l1 += p2 + p3;
                p[j * 2 + 0] = pack_bf16(p0, p1);
                p[j * 2 + 1] = pack_bf16(p2, p3);
            }
        }
        for (int it = 1; it < NT; it++) {
            int s = it % A_KV_STAGES;
            uint32_t ph = (it / A_KV_STAGES) & 1;
            int sp = (it - 1) % A_KV_STAGES;
            uint32_t php = ((it - 1) / A_KV_STAGES) & 1;
            mbar_wait(bar_kf + 8 * s, ph);
            named_sync(1 + cw, 256);
            uint32_t kb = sK + s * A_TILE_BYTES;
            wgmma_fence();
#pragma unroll
            for (int kk = 0; kk < 8; kk++) {
                uint32_t off = (kk >> 2) * 16384 + (kk & 3) * 32;
                wgmma_m64n128k16_ss<0, 0>(sacc, make_desc(qa + off, 16, 1024), make_desc(kb + off, 16, 1024), kk != 0);
            }
            wgmma_commit();
            mbar_wait(bar_vf + 8 * sp, php);
            uint32_t vb = sV + sp * A_TILE_BYTES;
#pragma unroll
            for (int kk = 0; kk < 8; kk++) {
                wgmma_m64n128k16_rs<1>(o, p[kk * 4 + 0], p[kk * 4 + 1], p[kk * 4 + 2], p[kk * 4 + 3],
                                       make_desc(vb + kk * 2048, 16384, 1024), 1);
            }
            wgmma_commit();
            named_arrive(1 + (cw ^ 1), 256);
            wgmma_wait<1>();
            if (lane == 0) mbar_arrive(bar_ke + 8 * s);
            float mx0 = m0, mx1 = m1;
#pragma unroll
            for (int j = 0; j < 16; j++) {
                mx0 = fmaxf(mx0, fmaxf(sacc[j * 4 + 0], sacc[j * 4 + 1]));
                mx1 = fmaxf(mx1, fmaxf(sacc[j * 4 + 2], sacc[j * 4 + 3]));
            }
            mx0 = fmaxf(mx0, __shfl_xor_sync(0xffffffffu, mx0, 1));
            mx0 = fmaxf(mx0, __shfl_xor_sync(0xffffffffu, mx0, 2));
            mx1 = fmaxf(mx1, __shfl_xor_sync(0xffffffffu, mx1, 1));
            mx1 = fmaxf(mx1, __shfl_xor_sync(0xffffffffu, mx1, 2));
            float c0 = fast_exp2((m0 - mx0) * sc), c1 = fast_exp2((m1 - mx1) * sc);
            m0 = mx0; m1 = mx1;
            float ms0 = mx0 * sc, ms1 = mx1 * sc;
            float rs0 = 0.f, rs1 = 0.f;
#pragma unroll
            for (int j = 0; j < 16; j++) {
                sacc[j * 4 + 0] = fast_exp2(sacc[j * 4 + 0] * sc - ms0);
                sacc[j * 4 + 1] = fast_exp2(sacc[j * 4 + 1] * sc - ms0);
                sacc[j * 4 + 2] = fast_exp2(sacc[j * 4 + 2] * sc - ms1);
                sacc[j * 4 + 3] = fast_exp2(sacc[j * 4 + 3] * sc - ms1);
                rs0 += sacc[j * 4 + 0] + sacc[j * 4 + 1]; rs1 += sacc[j * 4 + 2] + sacc[j * 4 + 3];
            }
            l0 = l0 * c0 + rs0; l1 = l1 * c1 + rs1;
            wgmma_wait<0>();
            if (lane == 0) mbar_arrive(bar_ve + 8 * sp);
#pragma unroll
            for (int j = 0; j < 16; j++) {
                o[j * 4 + 0] *= c0; o[j * 4 + 1] *= c0; o[j * 4 + 2] *= c1; o[j * 4 + 3] *= c1;
                p[j * 2 + 0] = pack_bf16(sacc[j * 4 + 0], sacc[j * 4 + 1]);
                p[j * 2 + 1] = pack_bf16(sacc[j * 4 + 2], sacc[j * 4 + 3]);
            }
        }
        {
            int sp = (NT - 1) % A_KV_STAGES;
            uint32_t php = ((NT - 1) / A_KV_STAGES) & 1;
            mbar_wait(bar_vf + 8 * sp, php);
            uint32_t vb = sV + sp * A_TILE_BYTES;
            wgmma_fence();
#pragma unroll
            for (int kk = 0; kk < 8; kk++) {
                wgmma_m64n128k16_rs<1>(o, p[kk * 4 + 0], p[kk * 4 + 1], p[kk * 4 + 2], p[kk * 4 + 3],
                                       make_desc(vb + kk * 2048, 16384, 1024), 1);
            }
            wgmma_commit();
            wgmma_wait<0>();
        }
        l0 += __shfl_xor_sync(0xffffffffu, l0, 1);
        l0 += __shfl_xor_sync(0xffffffffu, l0, 2);
        l1 += __shfl_xor_sync(0xffffffffu, l1, 1);
        l1 += __shfl_xor_sync(0xffffffffu, l1, 2);
        float i0 = 1.f / l0, i1 = 1.f / l1;
        {
            int r = cw * 64 + warp * 16 + (lane >> 2);
#pragma unroll
            for (int j = 0; j < 16; j++) {
                uint32_t a = sQ + (j >> 3) * 16384 + r * 128 + (((j & 7) ^ (r & 7)) << 4) + (lane & 3) * 4;
                st_shared_u32(a, pack_bf16(o[j * 4 + 0] * i0, o[j * 4 + 1] * i0));
                st_shared_u32(a + 1024, pack_bf16(o[j * 4 + 2] * i1, o[j * 4 + 3] * i1));
            }
            named_sync(3 + cw, 128);
#pragma unroll
            for (int i = 0; i < 8; i++) {
                int idx = i * 128 + tid;
                int rr = cw * 64 + (idx >> 4), ch = idx & 15;
                uint32_t a = sQ + (ch >> 3) * 16384 + rr * 128 + (((ch & 7) ^ (rr & 7)) << 4);
                uint4 v = ld_shared_v4(a);
                *reinterpret_cast<uint4*>(g_o + (size_t)(qt * 128 + rr) * HD + head * DH + ch * 8) = v;
            }
        }
    }
}

constexpr int F_STAGES = 8;
constexpr int F_SMEM = F_STAGES * G_STAGE_BYTES + 1024 + 256;
__global__ void __cluster_dims__(1, 2, 1) __launch_bounds__(256, 1)
final_kernel(const __grid_constant__ CUtensorMap mapO, const __grid_constant__ CUtensorMap mapWo,
             const __grid_constant__ CUtensorMap mapH, const __grid_constant__ CUtensorMap mapW2,
             const bf16* __restrict__ x, const bf16* __restrict__ b2, bf16* __restrict__ out) {
    extern __shared__ uint8_t smem_raw[];
    uint32_t sbase = (smem_u32(smem_raw) + 1023) & ~1023u;
    uint32_t bar_full = sbase + F_STAGES * G_STAGE_BYTES;
    uint32_t bar_empty = bar_full + 8 * F_STAGES;
    int wg = threadIdx.x >> 7;
    int tid = threadIdx.x & 127;
    int m0 = blockIdx.y * 64, n0 = blockIdx.x * 128;
    constexpr int NK1 = HD / 64;
    constexpr int NK2 = (FF + 63) / 64;

    if (threadIdx.x == 0) {
        for (int i = 0; i < F_STAGES; i++) { mbar_init(bar_full + 8 * i, 1); mbar_init(bar_empty + 8 * i, 8); }
        fence_barrier_init();
    }
    cluster_sync_all();
    uint32_t rank = cluster_ctarank();

    if (wg == 0) {
        if (tid == 0) {
            for (int it = 0; it < NK1 + NK2; it++) {
                int s = it % F_STAGES;
                uint32_t ph = (it / F_STAGES) & 1;
                mbar_wait(bar_empty + 8 * s, ph ^ 1);
                mbar_expect_tx(bar_full + 8 * s, G_STAGE_BYTES);
                uint32_t a = sbase + s * G_STAGE_BYTES;
                const CUtensorMap* pa = it < NK2 ? &mapH : &mapO;
                const CUtensorMap* pb = it < NK2 ? &mapW2 : &mapWo;
                int k = (it < NK2 ? it : it - NK2) * 64;
                tma_load_2d(a, pa, bar_full + 8 * s, k, m0);
                tma_load_2d_mc(a + 8192 + rank * 8192, pb, bar_full + 8 * s, n0 + rank * 64, k, 3);
            }
        }
    } else {
        float acc[64], acc2[64];
        int warp = tid >> 5, lane = tid & 31;
        int r = warp * 16 + (lane >> 2);
        uint32_t xv[32], bv[16];
#pragma unroll
        for (int j = 0; j < 16; j++) {
            int c = n0 + j * 8 + (lane & 3) * 2;
            bv[j] = *reinterpret_cast<const uint32_t*>(b2 + c);
            xv[j * 2] = *reinterpret_cast<const uint32_t*>(x + (size_t)(m0 + r) * DM + c);
            xv[j * 2 + 1] = *reinterpret_cast<const uint32_t*>(x + (size_t)(m0 + r + 8) * DM + c);
        }
        for (int it = 0; it < NK2; it++) {
            int s = it % F_STAGES;
            uint32_t ph = (it / F_STAGES) & 1;
            mbar_wait(bar_full + 8 * s, ph);
            uint32_t a = sbase + s * G_STAGE_BYTES;
            uint32_t b = a + 8192;
            wgmma_fence();
#pragma unroll
            for (int kk = 0; kk < 4; kk++)
                wgmma_m64n128k16_ss<0, 1>(acc2, make_desc(a + kk * 32, 16, 1024), make_desc(b + kk * 2048, 8192, 1024), (it | kk) != 0);
            wgmma_commit();
            wgmma_wait<1>();
            if (it > 0 && lane < 2) mbar_arrive_cluster(bar_empty + 8 * ((it - 1) % F_STAGES), lane);
        }
        for (int it = NK2; it < NK1 + NK2; it++) {
            int s = it % F_STAGES;
            uint32_t ph = (it / F_STAGES) & 1;
            mbar_wait(bar_full + 8 * s, ph);
            uint32_t a = sbase + s * G_STAGE_BYTES;
            uint32_t b = a + 8192;
            wgmma_fence();
#pragma unroll
            for (int kk = 0; kk < 4; kk++)
                wgmma_m64n128k16_ss<0, 1>(acc, make_desc(a + kk * 32, 16, 1024), make_desc(b + kk * 2048, 8192, 1024), ((it - NK2) | kk) != 0);
            wgmma_commit();
            wgmma_wait<1>();
            if (lane < 2) mbar_arrive_cluster(bar_empty + 8 * ((it - 1) % F_STAGES), lane);
        }
        wgmma_wait<0>();
#pragma unroll
        for (int j = 0; j < 16; j++) {
            float2 bf = __bfloat1622float2(*reinterpret_cast<const __nv_bfloat162*>(&bv[j]));
            uint32_t a = sbase + r * 256 + ((j ^ (r & 7)) << 4) + (lane & 3) * 4;
#pragma unroll
            for (int h = 0; h < 2; h++) {
                float2 xf = __bfloat1622float2(*reinterpret_cast<const __nv_bfloat162*>(&xv[j * 2 + h]));
                float g0 = acc2[j * 4 + h * 2 + 0] + bf.x, g1 = acc2[j * 4 + h * 2 + 1] + bf.y;
                g0 = __fdividef(g0, 1.f + __expf(-g0)); g1 = __fdividef(g1, 1.f + __expf(-g1));
                st_shared_u32(a + h * 2048, pack_bf16(xf.x + acc[j * 4 + h * 2 + 0] * g0, xf.y + acc[j * 4 + h * 2 + 1] * g1));
            }
        }
        named_sync(1, 128);
#pragma unroll
        for (int i = 0; i < 8; i++) {
            int idx = i * 128 + tid;
            int rr = idx >> 4, ch = idx & 15;
            uint4 v = ld_shared_v4(sbase + rr * 256 + ((ch ^ (rr & 7)) << 4));
            *reinterpret_cast<uint4*>(out + (size_t)(m0 + rr) * DM + n0 + ch * 8) = v;
        }
    }
    cluster_sync_all();
}

typedef CUresult (*EncodeFn)(CUtensorMap*, CUtensorMapDataType, cuuint32_t, void*, const cuuint64_t*, const cuuint64_t*,
                             const cuuint32_t*, const cuuint32_t*, CUtensorMapInterleave, CUtensorMapSwizzle,
                             CUtensorMapL2promotion, CUtensorMapFloatOOBfill);

static void make_map(EncodeFn fn, CUtensorMap* m, const void* ptr, uint64_t inner, uint64_t outer,
                     uint32_t box_inner, uint32_t box_outer) {
    cuuint64_t dims[2] = {inner, outer};
    cuuint64_t strides[1] = {inner * 2};
    cuuint32_t box[2] = {box_inner, box_outer};
    cuuint32_t es[2] = {1, 1};
    fn(m, CU_TENSOR_MAP_DATA_TYPE_BFLOAT16, 2, const_cast<void*>(ptr), dims, strides, box, es,
       CU_TENSOR_MAP_INTERLEAVE_NONE, CU_TENSOR_MAP_SWIZZLE_128B, CU_TENSOR_MAP_L2_PROMOTION_L2_256B,
       CU_TENSOR_MAP_FLOAT_OOB_FILL_NONE);
}

extern "C" void kernel_launch(void* const* d_in, const int* in_sizes, int n_in, void* d_out, int out_size) {
    const bf16* x  = (const bf16*)d_in[0];
    const bf16* kc = (const bf16*)d_in[1];
    const bf16* vc = (const bf16*)d_in[2];
    const bf16* wq = (const bf16*)d_in[3];
    const bf16* wo = (const bf16*)d_in[4];
    const bf16* w1 = (const bf16*)d_in[6];
    const bf16* b1 = (const bf16*)d_in[7];
    const bf16* w2 = (const bf16*)d_in[8];
    const bf16* b2 = (const bf16*)d_in[9];
    bf16* out = (bf16*)d_out;

    static bool inited = false;
    static CUtensorMap mXn, mY, mWq, mW1, mQ, mK, mV, mO, mWo, mH, mW2;
    static void *pq, *ph;
    static cudaStream_t s2;
    static cudaEvent_t evFork, evJoin;
    if (!inited) {
        EncodeFn fn = nullptr;
        cudaDriverEntryPointQueryResult qres;
        cudaGetDriverEntryPoint("cuTensorMapEncodeTiled", (void**)&fn, cudaEnableDefault, &qres);
        void *pxn, *py, *po;
        cudaGetSymbolAddress(&pxn, g_xn); cudaGetSymbolAddress(&py, g_y); cudaGetSymbolAddress(&pq, g_q);
        cudaGetSymbolAddress(&ph, g_h); cudaGetSymbolAddress(&po, g_o);
        make_map(fn, &mXn, pxn, DM, SEQ, 64, 128);
        make_map(fn, &mY, py, DM, SEQ, 64, 64);
        make_map(fn, &mWq, wq, HD, DM, 64, 64);
        make_map(fn, &mW1, w1, FF, DM, 64, 64);
        make_map(fn, &mK, kc, DH, NH * SEQ, 64, 128);
        make_map(fn, &mV, vc, DH, NH * SEQ, 64, 128);
        make_map(fn, &mO, po, HD, SEQ, 64, 64);
        make_map(fn, &mWo, wo, DM, HD, 64, 64);
        make_map(fn, &mH, ph, FF, SEQ, 64, 64);
        make_map(fn, &mW2, w2, DM, FF, 64, 64);
        cudaFuncSetAttribute(mlp1_kernel, cudaFuncAttributeMaxDynamicSharedMemorySize, M1_SMEM);
        cudaFuncSetAttribute(final_kernel, cudaFuncAttributeMaxDynamicSharedMemorySize, F_SMEM);
        cudaFuncSetAttribute(attn_kernel, cudaFuncAttributeMaxDynamicSharedMemorySize, A_SMEM);
        cudaStreamCreateWithFlags(&s2, cudaStreamNonBlocking);
        cudaEventCreateWithFlags(&evFork, cudaEventDisableTiming);
        cudaEventCreateWithFlags(&evJoin, cudaEventDisableTiming);
        inited = true;
    }

    ln_kernel<<<SEQ / 8, 256>>>(x);
    cudaEventRecord(evFork, cudaStreamPerThread);
    attn_kernel<<<dim3(SEQ / 128, NH), 384, A_SMEM>>>(mXn, mWq, mK, mV);
    cudaStreamWaitEvent(s2, evFork, 0);
    mlp1_kernel<<<dim3((FF + 127) / 128, SEQ / 64), 256, M1_SMEM, s2>>>(mY, mW1, (bf16*)ph, b1);
    cudaEventRecord(evJoin, s2);
    cudaStreamWaitEvent(cudaStreamPerThread, evJoin, 0);
    final_kernel<<<dim3(DM / 128, SEQ / 64), 256, F_SMEM>>>(mO, mWo, mH, mW2, x, b2, out);
}
```

```cpp
#include <cuda_runtime.h>
#include <cuda_bf16.h>
#include <cuda.h>
#include <stdint.h>

typedef __nv_bfloat16 bf16;

constexpr int SEQ = 2048;
constexpr int DM  = 512;
constexpr int NH  = 32;
constexpr int DH  = 128;
constexpr int HD  = NH * DH;
constexpr int FF  = 1376;

__device__ bf16 g_xn[SEQ * DM];
__device__ bf16 g_y [SEQ * DM];
__device__ bf16 g_q [SEQ * HD];
__device__ bf16 g_h [SEQ * FF];
__device__ bf16 g_o [SEQ * HD];

__device__ __forceinline__ uint32_t smem_u32(const void* p) {
    return (uint32_t)__cvta_generic_to_shared(p);
}
__device__ __forceinline__ void mbar_init(uint32_t bar, uint32_t count) {
    asm volatile("mbarrier.init.shared::cta.b64 [%0], %1;" :: "r"(bar), "r"(count) : "memory");
}
__device__ __forceinline__ void mbar_arrive(uint32_t bar) {
    asm volatile("mbarrier.arrive.shared::cta.b64 _, [%0];" :: "r"(bar) : "memory");
}
__device__ __forceinline__ void mbar_expect_tx(uint32_t bar, uint32_t bytes) {
    asm volatile("mbarrier.arrive.expect_tx.shared::cta.b64 _, [%0], %1;" :: "r"(bar), "r"(bytes) : "memory");
}
__device__ __forceinline__ void mbar_wait(uint32_t bar, uint32_t parity) {
    asm volatile(
        "{\n"
        ".reg .pred p;\n"
        "LAB_WAIT:\n"
        "mbarrier.try_wait.parity.shared::cta.b64 p, [%0], %1;\n"
        "@p bra DONE;\n"
        "bra LAB_WAIT;\n"
        "DONE:\n"
        "}\n" :: "r"(bar), "r"(parity) : "memory");
}
__device__ __forceinline__ void tma_load_2d(uint32_t dst, const CUtensorMap* map, uint32_t bar, int c0, int c1) {
    asm volatile(
        "cp.async.bulk.tensor.2d.shared::cluster.global.mbarrier::complete_tx::bytes [%0], [%1, {%3, %4}], [%2];"
        :: "r"(dst), "l"((uint64_t)map), "r"(bar), "r"(c0), "r"(c1) : "memory");
}
__device__ __forceinline__ void wgmma_fence() { asm volatile("wgmma.fence.sync.aligned;" ::: "memory"); }
__device__ __forceinline__ void wgmma_commit() { asm volatile("wgmma.commit_group.sync.aligned;" ::: "memory"); }
template <int N> __device__ __forceinline__ void wgmma_wait() {
    asm volatile("wgmma.wait_group.sync.aligned %0;" :: "n"(N) : "memory");
}
template <int R> __device__ __forceinline__ void reg_alloc() {
    asm volatile("setmaxnreg.inc.sync.aligned.u32 %0;" :: "n"(R));
}
template <int R> __device__ __forceinline__ void reg_dealloc() {
    asm volatile("setmaxnreg.dec.sync.aligned.u32 %0;" :: "n"(R));
}
__device__ __forceinline__ void fence_barrier_init() {
    asm volatile("fence.mbarrier_init.release.cluster;" ::: "memory");
}
__device__ __forceinline__ void fence_proxy_async() {
    asm volatile("fence.proxy.async.shared::cta;" ::: "memory");
}

__device__ __forceinline__ void named_sync(int id, int n) {
    asm volatile("bar.sync %0, %1;" :: "r"(id), "r"(n) : "memory");
}
__device__ __forceinline__ void named_arrive(int id, int n) {
    asm volatile("bar.arrive %0, %1;" :: "r"(id), "r"(n) : "memory");
}
__device__ __forceinline__ float fast_exp2(float x) {
    float y;
    asm("ex2.approx.ftz.f32 %0, %1;" : "=f"(y) : "f"(x));
    return y;
}

__device__ __forceinline__ void st_shared_u32(uint32_t a, uint32_t v) {
    asm volatile("st.shared.u32 [%0], %1;" :: "r"(a), "r"(v) : "memory");
}
__device__ __forceinline__ uint4 ld_shared_v4(uint32_t a) {
    uint4 v;
    asm volatile("ld.shared.v4.u32 {%0,%1,%2,%3}, [%4];" : "=r"(v.x), "=r"(v.y), "=r"(v.z), "=r"(v.w) : "r"(a) : "memory");
    return v;
}

__device__ __forceinline__ uint64_t make_desc(uint32_t addr, uint32_t lbo_bytes, uint32_t sbo_bytes) {
    uint64_t d = 0;
    d |= (uint64_t)((addr & 0x3FFFF) >> 4);
    d |= (uint64_t)((lbo_bytes & 0x3FFFF) >> 4) << 16;
    d |= (uint64_t)((sbo_bytes & 0x3FFFF) >> 4) << 32;
    d |= (uint64_t)1 << 62;
    return d;
}

template <int TA, int TB>
__device__ __forceinline__ void wgmma_m64n128k16_ss(float (&d)[64], uint64_t da, uint64_t db, int scale_d) {
    asm volatile(
        "{\n.reg .pred p;\nsetp.ne.b32 p, %66, 0;\n"
        "wgmma.mma_async.sync.aligned.m64n128k16.f32.bf16.bf16 "
        "{%0,%1,%2,%3,%4,%5,%6,%7,%8,%9,%10,%11,%12,%13,%14,%15,"
        "%16,%17,%18,%19,%20,%21,%22,%23,%24,%25,%26,%27,%28,%29,%30,%31,"
        "%32,%33,%34,%35,%36,%37,%38,%39,%40,%41,%42,%43,%44,%45,%46,%47,"
        "%48,%49,%50,%51,%52,%53,%54,%55,%56,%57,%58,%59,%60,%61,%62,%63},"
        " %64, %65, p, 1, 1, %67, %68;\n}\n"
        : "+f"(d[0]), "+f"(d[1]), "+f"(d[2]), "+f"(d[3]), "+f"(d[4]), "+f"(d[5]), "+f"(d[6]), "+f"(d[7]),
          "+f"(d[8]), "+f"(d[9]), "+f"(d[10]), "+f"(d[11]), "+f"(d[12]), "+f"(d[13]), "+f"(d[14]), "+f"(d[15]),
          "+f"(d[16]), "+f"(d[17]), "+f"(d[18]), "+f"(d[19]), "+f"(d[20]), "+f"(d[21]), "+f"(d[22]), "+f"(d[23]),
          "+f"(d[24]), "+f"(d[25]), "+f"(d[26]), "+f"(d[27]), "+f"(d[28]), "+f"(d[29]), "+f"(d[30]), "+f"(d[31]),
          "+f"(d[32]), "+f"(d[33]), "+f"(d[34]), "+f"(d[35]), "+f"(d[36]), "+f"(d[37]), "+f"(d[38]), "+f"(d[39]),
          "+f"(d[40]), "+f"(d[41]), "+f"(d[42]), "+f"(d[43]), "+f"(d[44]), "+f"(d[45]), "+f"(d[46]), "+f"(d[47]),
          "+f"(d[48]), "+f"(d[49]), "+f"(d[50]), "+f"(d[51]), "+f"(d[52]), "+f"(d[53]), "+f"(d[54]), "+f"(d[55]),
          "+f"(d[56]), "+f"(d[57]), "+f"(d[58]), "+f"(d[59]), "+f"(d[60]), "+f"(d[61]), "+f"(d[62]), "+f"(d[63])
        : "l"(da), "l"(db), "r"(scale_d), "n"(TA), "n"(TB));
}

template <int TB>
__device__ __forceinline__ void wgmma_m64n128k16_rs(float (&d)[64], uint32_t a0, uint32_t a1, uint32_t a2, uint32_t a3,
                                                    uint64_t db, int scale_d) {
    asm volatile(
        "{\n.reg .pred p;\nsetp.ne.b32 p, %69, 0;\n"
        "wgmma.mma_async.sync.aligned.m64n128k16.f32.bf16.bf16 "
        "{%0,%1,%2,%3,%4,%5,%6,%7,%8,%9,%10,%11,%12,%13,%14,%15,"
        "%16,%17,%18,%19,%20,%21,%22,%23,%24,%25,%26,%27,%28,%29,%30,%31,"
        "%32,%33,%34,%35,%36,%37,%38,%39,%40,%41,%42,%43,%44,%45,%46,%47,"
        "%48,%49,%50,%51,%52,%53,%54,%55,%56,%57,%58,%59,%60,%61,%62,%63},"
        " {%64,%65,%66,%67}, %68, p, 1, 1, %70;\n}\n"
        : "+f"(d[0]), "+f"(d[1]), "+f"(d[2]), "+f"(d[3]), "+f"(d[4]), "+f"(d[5]), "+f"(d[6]), "+f"(d[7]),
          "+f"(d[8]), "+f"(d[9]), "+f"(d[10]), "+f"(d[11]), "+f"(d[12]), "+f"(d[13]), "+f"(d[14]), "+f"(d[15]),
          "+f"(d[16]), "+f"(d[17]), "+f"(d[18]), "+f"(d[19]), "+f"(d[20]), "+f"(d[21]), "+f"(d[22]), "+f"(d[23]),
          "+f"(d[24]), "+f"(d[25]), "+f"(d[26]), "+f"(d[27]), "+f"(d[28]), "+f"(d[29]), "+f"(d[30]), "+f"(d[31]),
          "+f"(d[32]), "+f"(d[33]), "+f"(d[34]), "+f"(d[35]), "+f"(d[36]), "+f"(d[37]), "+f"(d[38]), "+f"(d[39]),
          "+f"(d[40]), "+f"(d[41]), "+f"(d[42]), "+f"(d[43]), "+f"(d[44]), "+f"(d[45]), "+f"(d[46]), "+f"(d[47]),
          "+f"(d[48]), "+f"(d[49]), "+f"(d[50]), "+f"(d[51]), "+f"(d[52]), "+f"(d[53]), "+f"(d[54]), "+f"(d[55]),
          "+f"(d[56]), "+f"(d[57]), "+f"(d[58]), "+f"(d[59]), "+f"(d[60]), "+f"(d[61]), "+f"(d[62]), "+f"(d[63])
        : "r"(a0), "r"(a1), "r"(a2), "r"(a3), "l"(db), "r"(scale_d), "n"(TB));
}

__device__ __forceinline__ uint32_t pack_bf16(float lo, float hi) {
    __nv_bfloat162 v = __floats2bfloat162_rn(lo, hi);
    return *reinterpret_cast<uint32_t*>(&v);
}

__global__ void __launch_bounds__(256) ln_kernel(const bf16* __restrict__ x) {
    int warp = threadIdx.x >> 5, lane = threadIdx.x & 31;
    int row = blockIdx.x * 8 + warp;
    const uint4* src = reinterpret_cast<const uint4*>(x + (size_t)row * DM);
    float v[16];
#pragma unroll
    for (int i = 0; i < 2; i++) {
        uint4 u = src[lane + i * 32];
        const __nv_bfloat162* h = reinterpret_cast<const __nv_bfloat162*>(&u);
#pragma unroll
        for (int j = 0; j < 4; j++) {
            float2 f = __bfloat1622float2(h[j]);
            v[i * 8 + j * 2] = f.x; v[i * 8 + j * 2 + 1] = f.y;
        }
    }
#pragma unroll
    for (int pass = 0; pass < 2; pass++) {
        float s = 0.f;
#pragma unroll
        for (int i = 0; i < 16; i++) s += v[i];
#pragma unroll
        for (int o = 16; o > 0; o >>= 1) s += __shfl_xor_sync(0xffffffffu, s, o);
        float mean = s * (1.f / DM);
        float q = 0.f;
#pragma unroll
        for (int i = 0; i < 16; i++) { float d = v[i] - mean; q += d * d; }
#pragma unroll
        for (int o = 16; o > 0; o >>= 1) q += __shfl_xor_sync(0xffffffffu, q, o);
        float rstd = 1.0f / sqrtf(q * (1.f / DM) + 1e-5f);
        bf16* dst = (pass == 0 ? g_xn : g_y) + (size_t)row * DM;
#pragma unroll
        for (int i = 0; i < 2; i++) {
            uint4 u;
            uint32_t* w = reinterpret_cast<uint32_t*>(&u);
#pragma unroll
            for (int j = 0; j < 4; j++) {
                __nv_bfloat162 h = __floats2bfloat162_rn((v[i * 8 + j * 2] - mean) * rstd, (v[i * 8 + j * 2 + 1] - mean) * rstd);
                w[j] = *reinterpret_cast<uint32_t*>(&h);
                float2 f = __bfloat1622float2(h);
                v[i * 8 + j * 2] = f.x; v[i * 8 + j * 2 + 1] = f.y;
            }
            reinterpret_cast<uint4*>(dst)[lane + i * 32] = u;
        }
    }
}

constexpr int G_STAGE_BYTES = 8192 + 16384;

__device__ __forceinline__ float gelu_tanh(float x) {
    float u = 0.7978845608028654f * (x + 0.044715f * x * x * x);
    float t = 1.f - __fdividef(2.f, 1.f + __expf(2.f * u));
    return 0.5f * x * (1.f + t);
}

constexpr int M1_STAGES = 4;
constexpr int M1_SMEM = M1_STAGES * G_STAGE_BYTES + 1024 + 256;
__global__ void __launch_bounds__(256, 2)
mlp1_kernel(const __grid_constant__ CUtensorMap mapA, const __grid_constant__ CUtensorMap mapB,
            bf16* __restrict__ C, const bf16* __restrict__ bias) {
    extern __shared__ uint8_t smem_raw[];
    uint32_t sbase = (smem_u32(smem_raw) + 1023) & ~1023u;
    uint32_t bar_full = sbase + M1_STAGES * G_STAGE_BYTES;
    uint32_t bar_empty = bar_full + 8 * M1_STAGES;
    int wg = threadIdx.x >> 7;
    int tid = threadIdx.x & 127;
    int m0 = blockIdx.y * 64, n0 = blockIdx.x * 128;
    constexpr int nk = DM / 64;

    if (threadIdx.x == 0) {
        for (int i = 0; i < M1_STAGES; i++) { mbar_init(bar_full + 8 * i, 1); mbar_init(bar_empty + 8 * i, 4); }
        fence_barrier_init();
    }
    __syncthreads();

    if (wg == 0) {
        if (tid == 0) {
            for (int it = 0; it < nk; it++) {
                int s = it % M1_STAGES;
                uint32_t ph = (it / M1_STAGES) & 1;
                mbar_wait(bar_empty + 8 * s, ph ^ 1);
                mbar_expect_tx(bar_full + 8 * s, G_STAGE_BYTES);
                uint32_t a = sbase + s * G_STAGE_BYTES;
                tma_load_2d(a, &mapA, bar_full + 8 * s, it * 64, m0);
                tma_load_2d(a + 8192, &mapB, bar_full + 8 * s, n0, it * 64);
                tma_load_2d(a + 8192 + 8192, &mapB, bar_full + 8 * s, n0 + 64, it * 64);
            }
        }
    } else {
        float acc[64];
        int warp = tid >> 5, lane = tid & 31;
        uint32_t bv[16];
#pragma unroll
        for (int j = 0; j < 16; j++) {
            int c = min(n0 + j * 8 + (lane & 3) * 2, FF - 2);
            bv[j] = *reinterpret_cast<const uint32_t*>(bias + c);
        }
        for (int it = 0; it < nk; it++) {
            int s = it % M1_STAGES;
            uint32_t ph = (it / M1_STAGES) & 1;
            mbar_wait(bar_full + 8 * s, ph);
            uint32_t a = sbase + s * G_STAGE_BYTES;
            uint32_t b = a + 8192;
            wgmma_fence();
#pragma unroll
            for (int kk = 0; kk < 4; kk++)
                wgmma_m64n128k16_ss<0, 1>(acc, make_desc(a + kk * 32, 16, 1024), make_desc(b + kk * 2048, 8192, 1024), (it | kk) != 0);
            wgmma_commit();
            wgmma_wait<1>();
            if (it > 0 && lane == 0) mbar_arrive(bar_empty + 8 * ((it - 1) % M1_STAGES));
        }
        wgmma_wait<0>();
        int r = warp * 16 + (lane >> 2);
#pragma unroll
        for (int j = 0; j < 16; j++) {
            float2 bf = __bfloat1622float2(*reinterpret_cast<const __nv_bfloat162*>(&bv[j]));
            float b0 = bf.x, b1 = bf.y;
            uint32_t a = sbase + r * 256 + ((j ^ (r & 7)) << 4) + (lane & 3) * 4;
            st_shared_u32(a, pack_bf16(gelu_tanh(acc[j * 4 + 0] + b0), gelu_tanh(acc[j * 4 + 1] + b1)));
            st_shared_u32(a + 2048, pack_bf16(gelu_tanh(acc[j * 4 + 2] + b0), gelu_tanh(acc[j * 4 + 3] + b1)));
        }
        named_sync(1, 128);
#pragma unroll
        for (int i = 0; i < 8; i++) {
            int idx = i * 128 + tid;
            int rr = idx >> 4, ch = idx & 15;
            uint4 v = ld_shared_v4(sbase + rr * 256 + ((ch ^ (rr & 7)) << 4));
            if (n0 + ch * 8 < FF)
                *reinterpret_cast<uint4*>(C + (size_t)(m0 + rr) * FF + n0 + ch * 8) = v;
        }
    }
}

constexpr int A_KV_STAGES = 2;
constexpr int A_TILE_BYTES = 128 * 128 * 2;
constexpr int A_SMEM = A_TILE_BYTES * (1 + 2 * A_KV_STAGES) + 1024 + 256;

__global__ void __launch_bounds__(384, 1)
attn_kernel(const __grid_constant__ CUtensorMap mapXn, const __grid_constant__ CUtensorMap mapWq,
            const __grid_constant__ CUtensorMap mapK, const __grid_constant__ CUtensorMap mapV) {
    extern __shared__ uint8_t smem_raw[];
    uint32_t sbase = (smem_u32(smem_raw) + 1023) & ~1023u;
    uint32_t sQ = sbase;
    uint32_t sK = sQ + A_TILE_BYTES;
    uint32_t sV = sK + A_KV_STAGES * A_TILE_BYTES;
    uint32_t bars = sV + A_KV_STAGES * A_TILE_BYTES;
    uint32_t bar_pf = bars, bar_pe = bars + 32;
    uint32_t bar_kf = bars + 64, bar_ke = bar_kf + 8 * A_KV_STAGES;
    uint32_t bar_vf = bar_ke + 8 * A_KV_STAGES, bar_ve = bar_vf + 8 * A_KV_STAGES;
    int wg = threadIdx.x >> 7;
    int tid = threadIdx.x & 127;
    constexpr int NTILES = (SEQ / 128) * NH;
    constexpr int NT = SEQ / 128;

    if (threadIdx.x == 0) {
        for (int i = 0; i < 4; i++) { mbar_init(bar_pf + 8 * i, 1); mbar_init(bar_pe + 8 * i, 8); }
        for (int i = 0; i < A_KV_STAGES; i++) {
            mbar_init(bar_kf + 8 * i, 1); mbar_init(bar_ke + 8 * i, 8);
            mbar_init(bar_vf + 8 * i, 1); mbar_init(bar_ve + 8 * i, 8);
        }
        fence_barrier_init();
    }
    __syncthreads();

    if (wg == 0) {
        reg_dealloc<40>();
        if (tid == 0) {
          for (int tile = blockIdx.x; tile < NTILES; tile += gridDim.x) {
            int qt = tile & 15, head = tile >> 4;
            for (int i = 0; i < 8; i++) {
                int b = i & 3;
                uint32_t buf = sK + b * A_TILE_BYTES;
                if (i < 4) mbar_wait((b < 2 ? bar_ke + 8 * b : bar_ve + 8 * (b - 2)), 1);
                mbar_wait(bar_pe + 8 * b, ((i >> 2) & 1) ^ 1);
                mbar_expect_tx(bar_pf + 8 * b, A_TILE_BYTES);
                tma_load_2d(buf, &mapXn, bar_pf + 8 * b, i * 64, qt * 128);
                tma_load_2d(buf + 16384, &mapWq, bar_pf + 8 * b, head * DH, i * 64);
                tma_load_2d(buf + 16384 + 8192, &mapWq, bar_pf + 8 * b, head * DH + 64, i * 64);
            }
            for (int it = 0; it < NT; it++) {
                int s = it % A_KV_STAGES;
                uint32_t ph = (it / A_KV_STAGES) & 1;
                int row = head * SEQ + it * 128;
                if (it < A_KV_STAGES) mbar_wait(bar_pe + 8 * s, 1);
                else mbar_wait(bar_ke + 8 * s, ph ^ 1);
                mbar_expect_tx(bar_kf + 8 * s, A_TILE_BYTES);
                tma_load_2d(sK + s * A_TILE_BYTES, &mapK, bar_kf + 8 * s, 0, row);
                tma_load_2d(sK + s * A_TILE_BYTES + 16384, &mapK, bar_kf + 8 * s, 64, row);
                if (it < A_KV_STAGES) mbar_wait(bar_pe + 8 * (A_KV_STAGES + s), 1);
                else mbar_wait(bar_ve + 8 * s, ph ^ 1);
                mbar_expect_tx(bar_vf + 8 * s, A_TILE_BYTES);
                tma_load_2d(sV + s * A_TILE_BYTES, &mapV, bar_vf + 8 * s, 0, row);
                tma_load_2d(sV + s * A_TILE_BYTES + 16384, &mapV, bar_vf + 8 * s, 64, row);
            }
          }
        }
    } else {
        reg_alloc<232>();
        int cw = wg - 1;
        int warp = tid >> 5, lane = tid & 31;
        float o[64];
        if (cw == 1) named_arrive(1, 256);
      for (int tile = blockIdx.x; tile < NTILES; tile += gridDim.x) {
        int qt = tile & 15, head = tile >> 4;
        for (int i = 0; i < 8; i++) {
            int b = i & 3;
            uint32_t buf = sK + b * A_TILE_BYTES;
            mbar_wait(bar_pf + 8 * b, (i >> 2) & 1);
            wgmma_fence();
#pragma unroll
            for (int kk = 0; kk < 4; kk++)
                wgmma_m64n128k16_ss<0, 1>(o, make_desc(buf + cw * 8192 + kk * 32, 16, 1024),
                                          make_desc(buf + 16384 + kk * 2048, 8192, 1024), (i | kk) != 0);
            wgmma_commit();
            wgmma_wait<0>();
            if (lane == 0) mbar_arrive(bar_pe + 8 * b);
        }
        {
            int r = cw * 64 + warp * 16 + (lane >> 2);
#pragma unroll
            for (int j = 0; j < 16; j++) {
                uint32_t a = sQ + (j >> 3) * 16384 + r * 128 + (((j & 7) ^ (r & 7)) << 4) + (lane & 3) * 4;
                st_shared_u32(a, pack_bf16(o[j * 4 + 0], o[j * 4 + 1]));
                st_shared_u32(a + 1024, pack_bf16(o[j * 4 + 2], o[j * 4 + 3]));
            }
            fence_proxy_async();
            named_sync(3 + cw, 128);
        }
#pragma unroll
        for (int i = 0; i < 64; i++) o[i] = 0.f;
        float m0 = -INFINITY, m1 = -INFINITY, l0 = 0.f, l1 = 0.f;
        const float sc = 0.08838834764831845f * 1.4426950408889634f;
        uint32_t qa = sQ + cw * 8192;
        float sacc[64];
        uint32_t p[32];
        mbar_wait(bar_kf, 0);
        named_sync(1 + cw, 256);
        wgmma_fence();
#pragma unroll
        for (int kk = 0; kk < 8; kk++) {
            uint32_t off = (kk >> 2) * 16384 + (kk & 3) * 32;
            wgmma_m64n128k16_ss<0, 0>(sacc, make_desc(qa + off, 16, 1024), make_desc(sK + off, 16, 1024), kk != 0);
        }
        wgmma_commit();
        named_arrive(1 + (cw ^ 1), 256);
        wgmma_wait<0>();
        if (lane == 0) mbar_arrive(bar_ke);
        {
            float mx0 = -INFINITY, mx1 = -INFINITY;
#pragma unroll
            for (int j = 0; j < 16; j++) {
                mx0 = fmaxf(mx0, fmaxf(sacc[j * 4 + 0], sacc[j * 4 + 1]));
                mx1 = fmaxf(mx1, fmaxf(sacc[j * 4 + 2], sacc[j * 4 + 3]));
            }
            mx0 = fmaxf(mx0, __shfl_xor_sync(0xffffffffu, mx0, 1));
            mx0 = fmaxf(mx0, __shfl_xor_sync(0xffffffffu, mx0, 2));
            mx1 = fmaxf(mx1, __shfl_xor_sync(0xffffffffu, mx1, 1));
            mx1 = fmaxf(mx1, __shfl_xor_sync(0xffffffffu, mx1, 2));
            m0 = mx0; m1 = mx1;
            float ms0 = mx0 * sc, ms1 = mx1 * sc;
#pragma unroll
            for (int j = 0; j < 16; j++) {
                float p0 = fast_exp2(sacc[j * 4 + 0] * sc - ms0);
                float p1 = fast_exp2(sacc[j * 4 + 1] * sc - ms0);
                float p2 = fast_exp2(sacc[j * 4 + 2] * sc - ms1);
                float p3 = fast_exp2(sacc[j * 4 + 3] * sc - ms1);
                l0 += p0 + p1; l1 += p2 + p3;
                p[j * 2 + 0] = pack_bf16(p0, p1);
                p[j * 2 + 1] = pack_bf16(p2, p3);
            }
        }
        for (int it = 1; it < NT; it++) {
            int s = it % A_KV_STAGES;
            uint32_t ph = (it / A_KV_STAGES) & 1;
            int sp = (it - 1) % A_KV_STAGES;
            uint32_t php = ((it - 1) / A_KV_STAGES) & 1;
            mbar_wait(bar_kf + 8 * s, ph);
            named_sync(1 + cw, 256);
            uint32_t kb = sK + s * A_TILE_BYTES;
            wgmma_fence();
#pragma unroll
            for (int kk = 0; kk < 8; kk++) {
                uint32_t off = (kk >> 2) * 16384 + (kk & 3) * 32;
                wgmma_m64n128k16_ss<0, 0>(sacc, make_desc(qa + off, 16, 1024), make_desc(kb + off, 16, 1024), kk != 0);
            }
            wgmma_commit();
            mbar_wait(bar_vf + 8 * sp, php);
            uint32_t vb = sV + sp * A_TILE_BYTES;
#pragma unroll
            for (int kk = 0; kk < 8; kk++) {
                wgmma_m64n128k16_rs<1>(o, p[kk * 4 + 0], p[kk * 4 + 1], p[kk * 4 + 2], p[kk * 4 + 3],
                                       make_desc(vb + kk * 2048, 16384, 1024), 1);
            }
            wgmma_commit();
            named_arrive(1 + (cw ^ 1), 256);
            wgmma_wait<1>();
            if (lane == 0) mbar_arrive(bar_ke + 8 * s);
            float mx0 = m0, mx1 = m1;
#pragma unroll
            for (int j = 0; j < 16; j++) {
                mx0 = fmaxf(mx0, fmaxf(sacc[j * 4 + 0], sacc[j * 4 + 1]));
                mx1 = fmaxf(mx1, fmaxf(sacc[j * 4 + 2], sacc[j * 4 + 3]));
            }
            mx0 = fmaxf(mx0, __shfl_xor_sync(0xffffffffu, mx0, 1));
            mx0 = fmaxf(mx0, __shfl_xor_sync(0xffffffffu, mx0, 2));
            mx1 = fmaxf(mx1, __shfl_xor_sync(0xffffffffu, mx1, 1));
            mx1 = fmaxf(mx1, __shfl_xor_sync(0xffffffffu, mx1, 2));
            float c0 = fast_exp2((m0 - mx0) * sc), c1 = fast_exp2((m1 - mx1) * sc);
            m0 = mx0; m1 = mx1;
            float ms0 = mx0 * sc, ms1 = mx1 * sc;
            float rs0 = 0.f, rs1 = 0.f;
#pragma unroll
            for (int j = 0; j < 16; j++) {
                sacc[j * 4 + 0] = fast_exp2(sacc[j * 4 + 0] * sc - ms0);
                sacc[j * 4 + 1] = fast_exp2(sacc[j * 4 + 1] * sc - ms0);
                sacc[j * 4 + 2] = fast_exp2(sacc[j * 4 + 2] * sc - ms1);
                sacc[j * 4 + 3] = fast_exp2(sacc[j * 4 + 3] * sc - ms1);
                rs0 += sacc[j * 4 + 0] + sacc[j * 4 + 1]; rs1 += sacc[j * 4 + 2] + sacc[j * 4 + 3];
            }
            l0 = l0 * c0 + rs0; l1 = l1 * c1 + rs1;
            wgmma_wait<0>();
            if (lane == 0) mbar_arrive(bar_ve + 8 * sp);
#pragma unroll
            for (int j = 0; j < 16; j++) {
                o[j * 4 + 0] *= c0; o[j * 4 + 1] *= c0; o[j * 4 + 2] *= c1; o[j * 4 + 3] *= c1;
                p[j * 2 + 0] = pack_bf16(sacc[j * 4 + 0], sacc[j * 4 + 1]);
                p[j * 2 + 1] = pack_bf16(sacc[j * 4 + 2], sacc[j * 4 + 3]);
            }
        }
        {
            int sp = (NT - 1) % A_KV_STAGES;
            uint32_t php = ((NT - 1) / A_KV_STAGES) & 1;
            mbar_wait(bar_vf + 8 * sp, php);
            uint32_t vb = sV + sp * A_TILE_BYTES;
            wgmma_fence();
#pragma unroll
            for (int kk = 0; kk < 8; kk++) {
                wgmma_m64n128k16_rs<1>(o, p[kk * 4 + 0], p[kk * 4 + 1], p[kk * 4 + 2], p[kk * 4 + 3],
                                       make_desc(vb + kk * 2048, 16384, 1024), 1);
            }
            wgmma_commit();
            wgmma_wait<0>();
            if (lane == 0) mbar_arrive(bar_ve + 8 * sp);
        }
        l0 += __shfl_xor_sync(0xffffffffu, l0, 1);
        l0 += __shfl_xor_sync(0xffffffffu, l0, 2);
        l1 += __shfl_xor_sync(0xffffffffu, l1, 1);
        l1 += __shfl_xor_sync(0xffffffffu, l1, 2);
        float i0 = 1.f / l0, i1 = 1.f / l1;
        {
            int r = cw * 64 + warp * 16 + (lane >> 2);
#pragma unroll
            for (int j = 0; j < 16; j++) {
                uint32_t a = sQ + (j >> 3) * 16384 + r * 128 + (((j & 7) ^ (r & 7)) << 4) + (lane & 3) * 4;
                st_shared_u32(a, pack_bf16(o[j * 4 + 0] * i0, o[j * 4 + 1] * i0));
                st_shared_u32(a + 1024, pack_bf16(o[j * 4 + 2] * i1, o[j * 4 + 3] * i1));
            }
            named_sync(3 + cw, 128);
#pragma unroll
            for (int i = 0; i < 8; i++) {
                int idx = i * 128 + tid;
                int rr = cw * 64 + (idx >> 4), ch = idx & 15;
                uint32_t a = sQ + (ch >> 3) * 16384 + rr * 128 + (((ch & 7) ^ (rr & 7)) << 4);
                uint4 v = ld_shared_v4(a);
                *reinterpret_cast<uint4*>(g_o + (size_t)(qt * 128 + rr) * HD + head * DH + ch * 8) = v;
            }
            named_sync(3 + cw, 128);
        }
      }
    }
}

constexpr int F_STAGES = 8;
constexpr int F_SMEM = F_STAGES * G_STAGE_BYTES + 1024 + 256;
__global__ void __launch_bounds__(256, 1)
final_kernel(const __grid_constant__ CUtensorMap mapO, const __grid_constant__ CUtensorMap mapWo,
             const __grid_constant__ CUtensorMap mapH, const __grid_constant__ CUtensorMap mapW2,
             const bf16* __restrict__ x, const bf16* __restrict__ b2, bf16* __restrict__ out) {
    extern __shared__ uint8_t smem_raw[];
    uint32_t sbase = (smem_u32(smem_raw) + 1023) & ~1023u;
    uint32_t bar_full = sbase + F_STAGES * G_STAGE_BYTES;
    uint32_t bar_empty = bar_full + 8 * F_STAGES;
    int wg = threadIdx.x >> 7;
    int tid = threadIdx.x & 127;
    int m0 = blockIdx.y * 64, n0 = blockIdx.x * 128;
    constexpr int NK1 = HD / 64;
    constexpr int NK2 = (FF + 63) / 64;

    if (threadIdx.x == 0) {
        for (int i = 0; i < F_STAGES; i++) { mbar_init(bar_full + 8 * i, 1); mbar_init(bar_empty + 8 * i, 4); }
        fence_barrier_init();
    }
    __syncthreads();

    if (wg == 0) {
        if (tid == 0) {
            for (int it = 0; it < NK1 + NK2; it++) {
                int s = it % F_STAGES;
                uint32_t ph = (it / F_STAGES) & 1;
                mbar_wait(bar_empty + 8 * s, ph ^ 1);
                mbar_expect_tx(bar_full + 8 * s, G_STAGE_BYTES);
                uint32_t a = sbase + s * G_STAGE_BYTES;
                const CUtensorMap* pa = it < NK2 ? &mapH : &mapO;
                const CUtensorMap* pb = it < NK2 ? &mapW2 : &mapWo;
                int k = (it < NK2 ? it : it - NK2) * 64;
                tma_load_2d(a, pa, bar_full + 8 * s, k, m0);
                tma_load_2d(a + 8192, pb, bar_full + 8 * s, n0, k);
                tma_load_2d(a + 8192 + 8192, pb, bar_full + 8 * s, n0 + 64, k);
            }
        }
    } else {
        float acc[64], acc2[64];
        int warp = tid >> 5, lane = tid & 31;
        int r = warp * 16 + (lane >> 2);
        uint32_t xv[32], bv[16];
#pragma unroll
        for (int j = 0; j < 16; j++) {
            int c = n0 + j * 8 + (lane & 3) * 2;
            bv[j] = *reinterpret_cast<const uint32_t*>(b2 + c);
            xv[j * 2] = *reinterpret_cast<const uint32_t*>(x + (size_t)(m0 + r) * DM + c);
            xv[j * 2 + 1] = *reinterpret_cast<const uint32_t*>(x + (size_t)(m0 + r + 8) * DM + c);
        }
        for (int it = 0; it < NK2; it++) {
            int s = it % F_STAGES;
            uint32_t ph = (it / F_STAGES) & 1;
            mbar_wait(bar_full + 8 * s, ph);
            uint32_t a = sbase + s * G_STAGE_BYTES;
            uint32_t b = a + 8192;
            wgmma_fence();
#pragma unroll
            for (int kk = 0; kk < 4; kk++)
                wgmma_m64n128k16_ss<0, 1>(acc2, make_desc(a + kk * 32, 16, 1024), make_desc(b + kk * 2048, 8192, 1024), (it | kk) != 0);
            wgmma_commit();
            wgmma_wait<1>();
            if (it > 0 && lane == 0) mbar_arrive(bar_empty + 8 * ((it - 1) % F_STAGES));
        }
        for (int it = NK2; it < NK1 + NK2; it++) {
            int s = it % F_STAGES;
            uint32_t ph = (it / F_STAGES) & 1;
            mbar_wait(bar_full + 8 * s, ph);
            uint32_t a = sbase + s * G_STAGE_BYTES;
            uint32_t b = a + 8192;
            wgmma_fence();
#pragma unroll
            for (int kk = 0; kk < 4; kk++)
                wgmma_m64n128k16_ss<0, 1>(acc, make_desc(a + kk * 32, 16, 1024), make_desc(b + kk * 2048, 8192, 1024), ((it - NK2) | kk) != 0);
            wgmma_commit();
            wgmma_wait<1>();
            if (lane == 0) mbar_arrive(bar_empty + 8 * ((it - 1) % F_STAGES));
        }
        wgmma_wait<0>();
#pragma unroll
        for (int j = 0; j < 16; j++) {
            float2 bf = __bfloat1622float2(*reinterpret_cast<const __nv_bfloat162*>(&bv[j]));
            uint32_t a = sbase + r * 256 + ((j ^ (r & 7)) << 4) + (lane & 3) * 4;
#pragma unroll
            for (int h = 0; h < 2; h++) {
                float2 xf = __bfloat1622float2(*reinterpret_cast<const __nv_bfloat162*>(&xv[j * 2 + h]));
                float g0 = acc2[j * 4 + h * 2 + 0] + bf.x, g1 = acc2[j * 4 + h * 2 + 1] + bf.y;
                g0 = __fdividef(g0, 1.f + __expf(-g0)); g1 = __fdividef(g1, 1.f + __expf(-g1));
                st_shared_u32(a + h * 2048, pack_bf16(xf.x + acc[j * 4 + h * 2 + 0] * g0, xf.y + acc[j * 4 + h * 2 + 1] * g1));
            }
        }
        named_sync(1, 128);
#pragma unroll
        for (int i = 0; i < 8; i++) {
            int idx = i * 128 + tid;
            int rr = idx >> 4, ch = idx & 15;
            uint4 v = ld_shared_v4(sbase + rr * 256 + ((ch ^ (rr & 7)) << 4));
            *reinterpret_cast<uint4*>(out + (size_t)(m0 + rr) * DM + n0 + ch * 8) = v;
        }
    }
}

typedef CUresult (*EncodeFn)(CUtensorMap*, CUtensorMapDataType, cuuint32_t, void*, const cuuint64_t*, const cuuint64_t*,
                             const cuuint32_t*, const cuuint32_t*, CUtensorMapInterleave, CUtensorMapSwizzle,
                             CUtensorMapL2promotion, CUtensorMapFloatOOBfill);

static void make_map(EncodeFn fn, CUtensorMap* m, const void* ptr, uint64_t inner, uint64_t outer,
                     uint32_t box_inner, uint32_t box_outer) {
    cuuint64_t dims[2] = {inner, outer};
    cuuint64_t strides[1] = {inner * 2};
    cuuint32_t box[2] = {box_inner, box_outer};
    cuuint32_t es[2] = {1, 1};
    fn(m, CU_TENSOR_MAP_DATA_TYPE_BFLOAT16, 2, const_cast<void*>(ptr), dims, strides, box, es,
       CU_TENSOR_MAP_INTERLEAVE_NONE, CU_TENSOR_MAP_SWIZZLE_128B, CU_TENSOR_MAP_L2_PROMOTION_L2_256B,
       CU_TENSOR_MAP_FLOAT_OOB_FILL_NONE);
}

extern "C" void kernel_launch(void* const* d_in, const int* in_sizes, int n_in, void* d_out, int out_size) {
    const bf16* x  = (const bf16*)d_in[0];
    const bf16* kc = (const bf16*)d_in[1];
    const bf16* vc = (const bf16*)d_in[2];
    const bf16* wq = (const bf16*)d_in[3];
    const bf16* wo = (const bf16*)d_in[4];
    const bf16* w1 = (const bf16*)d_in[6];
    const bf16* b1 = (const bf16*)d_in[7];
    const bf16* w2 = (const bf16*)d_in[8];
    const bf16* b2 = (const bf16*)d_in[9];
    bf16* out = (bf16*)d_out;

    static bool inited = false;
    static CUtensorMap mXn, mY, mWq, mW1, mQ, mK, mV, mO, mWo, mH, mW2;
    static void *pq, *ph;
    static cudaStream_t s2;
    static cudaEvent_t evFork, evJoin;
    if (!inited) {
        EncodeFn fn = nullptr;
        cudaDriverEntryPointQueryResult qres;
        cudaGetDriverEntryPoint("cuTensorMapEncodeTiled", (void**)&fn, cudaEnableDefault, &qres);
        void *pxn, *py, *po;
        cudaGetSymbolAddress(&pxn, g_xn); cudaGetSymbolAddress(&py, g_y); cudaGetSymbolAddress(&pq, g_q);
        cudaGetSymbolAddress(&ph, g_h); cudaGetSymbolAddress(&po, g_o);
        make_map(fn, &mXn, pxn, DM, SEQ, 64, 128);
        make_map(fn, &mY, py, DM, SEQ, 64, 64);
        make_map(fn, &mWq, wq, HD, DM, 64, 64);
        make_map(fn, &mW1, w1, FF, DM, 64, 64);
        make_map(fn, &mK, kc, DH, NH * SEQ, 64, 128);
        make_map(fn, &mV, vc, DH, NH * SEQ, 64, 128);
        make_map(fn, &mO, po, HD, SEQ, 64, 64);
        make_map(fn, &mWo, wo, DM, HD, 64, 64);
        make_map(fn, &mH, ph, FF, SEQ, 64, 64);
        make_map(fn, &mW2, w2, DM, FF, 64, 64);
        cudaFuncSetAttribute(mlp1_kernel, cudaFuncAttributeMaxDynamicSharedMemorySize, M1_SMEM);
        cudaFuncSetAttribute(final_kernel, cudaFuncAttributeMaxDynamicSharedMemorySize, F_SMEM);
        cudaFuncSetAttribute(attn_kernel, cudaFuncAttributeMaxDynamicSharedMemorySize, A_SMEM);
        cudaStreamCreateWithFlags(&s2, cudaStreamNonBlocking);
        cudaEventCreateWithFlags(&evFork, cudaEventDisableTiming);
        cudaEventCreateWithFlags(&evJoin, cudaEventDisableTiming);
        inited = true;
    }

    ln_kernel<<<SEQ / 8, 256>>>(x);
    cudaEventRecord(evFork, cudaStreamPerThread);
    attn_kernel<<<132, 384, A_SMEM>>>(mXn, mWq, mK, mV);
    cudaStreamWaitEvent(s2, evFork, 0);
    mlp1_kernel<<<dim3((FF + 127) / 128, SEQ / 64), 256, M1_SMEM, s2>>>(mY, mW1, (bf16*)ph, b1);
    cudaEventRecord(evJoin, s2);
    cudaStreamWaitEvent(cudaStreamPerThread, evJoin, 0);
    final_kernel<<<dim3(DM / 128, SEQ / 64), 256, F_SMEM>>>(mO, mWo, mH, mW2, x, b2, out);
}
```

```cpp
#include <cuda_runtime.h>
#include <cuda_bf16.h>
#include <cuda.h>
#include <stdint.h>

typedef __nv_bfloat16 bf16;

constexpr int SEQ = 2048;
constexpr int DM  = 512;
constexpr int NH  = 32;
constexpr int DH  = 128;
constexpr int HD  = NH * DH;
constexpr int FF  = 1376;

__device__ bf16 g_xn[SEQ * DM];
__device__ bf16 g_y [SEQ * DM];
__device__ bf16 g_q [SEQ * HD];
__device__ bf16 g_h [SEQ * FF];
__device__ bf16 g_o [SEQ * HD];

__device__ __forceinline__ uint32_t smem_u32(const void* p) {
    return (uint32_t)__cvta_generic_to_shared(p);
}
__device__ __forceinline__ void mbar_init(uint32_t bar, uint32_t count) {
    asm volatile("mbarrier.init.shared::cta.b64 [%0], %1;" :: "r"(bar), "r"(count) : "memory");
}
__device__ __forceinline__ void mbar_arrive(uint32_t bar) {
    asm volatile("mbarrier.arrive.shared::cta.b64 _, [%0];" :: "r"(bar) : "memory");
}
__device__ __forceinline__ void mbar_expect_tx(uint32_t bar, uint32_t bytes) {
    asm volatile("mbarrier.arrive.expect_tx.shared::cta.b64 _, [%0], %1;" :: "r"(bar), "r"(bytes) : "memory");
}
__device__ __forceinline__ void mbar_wait(uint32_t bar, uint32_t parity) {
    asm volatile(
        "{\n"
        ".reg .pred p;\n"
        "LAB_WAIT:\n"
        "mbarrier.try_wait.parity.shared::cta.b64 p, [%0], %1;\n"
        "@p bra DONE;\n"
        "bra LAB_WAIT;\n"
        "DONE:\n"
        "}\n" :: "r"(bar), "r"(parity) : "memory");
}
__device__ __forceinline__ void tma_load_2d(uint32_t dst, const CUtensorMap* map, uint32_t bar, int c0, int c1) {
    asm volatile(
        "cp.async.bulk.tensor.2d.shared::cluster.global.mbarrier::complete_tx::bytes [%0], [%1, {%3, %4}], [%2];"
        :: "r"(dst), "l"((uint64_t)map), "r"(bar), "r"(c0), "r"(c1) : "memory");
}
__device__ __forceinline__ void wgmma_fence() { asm volatile("wgmma.fence.sync.aligned;" ::: "memory"); }
__device__ __forceinline__ void wgmma_commit() { asm volatile("wgmma.commit_group.sync.aligned;" ::: "memory"); }
template <int N> __device__ __forceinline__ void wgmma_wait() {
    asm volatile("wgmma.wait_group.sync.aligned %0;" :: "n"(N) : "memory");
}
template <int R> __device__ __forceinline__ void reg_alloc() {
    asm volatile("setmaxnreg.inc.sync.aligned.u32 %0;" :: "n"(R));
}
template <int R> __device__ __forceinline__ void reg_dealloc() {
    asm volatile("setmaxnreg.dec.sync.aligned.u32 %0;" :: "n"(R));
}
__device__ __forceinline__ void fence_barrier_init() {
    asm volatile("fence.mbarrier_init.release.cluster;" ::: "memory");
}
__device__ __forceinline__ void fence_proxy_async() {
    asm volatile("fence.proxy.async.shared::cta;" ::: "memory");
}

__device__ __forceinline__ void named_sync(int id, int n) {
    asm volatile("bar.sync %0, %1;" :: "r"(id), "r"(n) : "memory");
}
__device__ __forceinline__ void named_arrive(int id, int n) {
    asm volatile("bar.arrive %0, %1;" :: "r"(id), "r"(n) : "memory");
}
__device__ __forceinline__ float fast_exp2(float x) {
    float y;
    asm("ex2.approx.ftz.f32 %0, %1;" : "=f"(y) : "f"(x));
    return y;
}

__device__ __forceinline__ void st_shared_u32(uint32_t a, uint32_t v) {
    asm volatile("st.shared.u32 [%0], %1;" :: "r"(a), "r"(v) : "memory");
}
__device__ __forceinline__ uint4 ld_shared_v4(uint32_t a) {
    uint4 v;
    asm volatile("ld.shared.v4.u32 {%0,%1,%2,%3}, [%4];" : "=r"(v.x), "=r"(v.y), "=r"(v.z), "=r"(v.w) : "r"(a) : "memory");
    return v;
}

__device__ __forceinline__ uint64_t make_desc(uint32_t addr, uint32_t lbo_bytes, uint32_t sbo_bytes) {
    uint64_t d = 0;
    d |= (uint64_t)((addr & 0x3FFFF) >> 4);
    d |= (uint64_t)((lbo_bytes & 0x3FFFF) >> 4) << 16;
    d |= (uint64_t)((sbo_bytes & 0x3FFFF) >> 4) << 32;
    d |= (uint64_t)1 << 62;
    return d;
}

template <int TA, int TB>
__device__ __forceinline__ void wgmma_m64n128k16_ss(float (&d)[64], uint64_t da, uint64_t db, int scale_d) {
    asm volatile(
        "{\n.reg .pred p;\nsetp.ne.b32 p, %66, 0;\n"
        "wgmma.mma_async.sync.aligned.m64n128k16.f32.bf16.bf16 "
        "{%0,%1,%2,%3,%4,%5,%6,%7,%8,%9,%10,%11,%12,%13,%14,%15,"
        "%16,%17,%18,%19,%20,%21,%22,%23,%24,%25,%26,%27,%28,%29,%30,%31,"
        "%32,%33,%34,%35,%36,%37,%38,%39,%40,%41,%42,%43,%44,%45,%46,%47,"
        "%48,%49,%50,%51,%52,%53,%54,%55,%56,%57,%58,%59,%60,%61,%62,%63},"
        " %64, %65, p, 1, 1, %67, %68;\n}\n"
        : "+f"(d[0]), "+f"(d[1]), "+f"(d[2]), "+f"(d[3]), "+f"(d[4]), "+f"(d[5]), "+f"(d[6]), "+f"(d[7]),
          "+f"(d[8]), "+f"(d[9]), "+f"(d[10]), "+f"(d[11]), "+f"(d[12]), "+f"(d[13]), "+f"(d[14]), "+f"(d[15]),
          "+f"(d[16]), "+f"(d[17]), "+f"(d[18]), "+f"(d[19]), "+f"(d[20]), "+f"(d[21]), "+f"(d[22]), "+f"(d[23]),
          "+f"(d[24]), "+f"(d[25]), "+f"(d[26]), "+f"(d[27]), "+f"(d[28]), "+f"(d[29]), "+f"(d[30]), "+f"(d[31]),
          "+f"(d[32]), "+f"(d[33]), "+f"(d[34]), "+f"(d[35]), "+f"(d[36]), "+f"(d[37]), "+f"(d[38]), "+f"(d[39]),
          "+f"(d[40]), "+f"(d[41]), "+f"(d[42]), "+f"(d[43]), "+f"(d[44]), "+f"(d[45]), "+f"(d[46]), "+f"(d[47]),
          "+f"(d[48]), "+f"(d[49]), "+f"(d[50]), "+f"(d[51]), "+f"(d[52]), "+f"(d[53]), "+f"(d[54]), "+f"(d[55]),
          "+f"(d[56]), "+f"(d[57]), "+f"(d[58]), "+f"(d[59]), "+f"(d[60]), "+f"(d[61]), "+f"(d[62]), "+f"(d[63])
        : "l"(da), "l"(db), "r"(scale_d), "n"(TA), "n"(TB));
}

template <int TB>
__device__ __forceinline__ void wgmma_m64n128k16_rs(float (&d)[64], uint32_t a0, uint32_t a1, uint32_t a2, uint32_t a3,
                                                    uint64_t db, int scale_d) {
    asm volatile(
        "{\n.reg .pred p;\nsetp.ne.b32 p, %69, 0;\n"
        "wgmma.mma_async.sync.aligned.m64n128k16.f32.bf16.bf16 "
        "{%0,%1,%2,%3,%4,%5,%6,%7,%8,%9,%10,%11,%12,%13,%14,%15,"
        "%16,%17,%18,%19,%20,%21,%22,%23,%24,%25,%26,%27,%28,%29,%30,%31,"
        "%32,%33,%34,%35,%36,%37,%38,%39,%40,%41,%42,%43,%44,%45,%46,%47,"
        "%48,%49,%50,%51,%52,%53,%54,%55,%56,%57,%58,%59,%60,%61,%62,%63},"
        " {%64,%65,%66,%67}, %68, p, 1, 1, %70;\n}\n"
        : "+f"(d[0]), "+f"(d[1]), "+f"(d[2]), "+f"(d[3]), "+f"(d[4]), "+f"(d[5]), "+f"(d[6]), "+f"(d[7]),
          "+f"(d[8]), "+f"(d[9]), "+f"(d[10]), "+f"(d[11]), "+f"(d[12]), "+f"(d[13]), "+f"(d[14]), "+f"(d[15]),
          "+f"(d[16]), "+f"(d[17]), "+f"(d[18]), "+f"(d[19]), "+f"(d[20]), "+f"(d[21]), "+f"(d[22]), "+f"(d[23]),
          "+f"(d[24]), "+f"(d[25]), "+f"(d[26]), "+f"(d[27]), "+f"(d[28]), "+f"(d[29]), "+f"(d[30]), "+f"(d[31]),
          "+f"(d[32]), "+f"(d[33]), "+f"(d[34]), "+f"(d[35]), "+f"(d[36]), "+f"(d[37]), "+f"(d[38]), "+f"(d[39]),
          "+f"(d[40]), "+f"(d[41]), "+f"(d[42]), "+f"(d[43]), "+f"(d[44]), "+f"(d[45]), "+f"(d[46]), "+f"(d[47]),
          "+f"(d[48]), "+f"(d[49]), "+f"(d[50]), "+f"(d[51]), "+f"(d[52]), "+f"(d[53]), "+f"(d[54]), "+f"(d[55]),
          "+f"(d[56]), "+f"(d[57]), "+f"(d[58]), "+f"(d[59]), "+f"(d[60]), "+f"(d[61]), "+f"(d[62]), "+f"(d[63])
        : "r"(a0), "r"(a1), "r"(a2), "r"(a3), "l"(db), "r"(scale_d), "n"(TB));
}

__device__ __forceinline__ uint32_t pack_bf16(float lo, float hi) {
    __nv_bfloat162 v = __floats2bfloat162_rn(lo, hi);
    return *reinterpret_cast<uint32_t*>(&v);
}

__global__ void __launch_bounds__(256) ln_kernel(const bf16* __restrict__ x) {
    int warp = threadIdx.x >> 5, lane = threadIdx.x & 31;
    int row = blockIdx.x * 8 + warp;
    asm volatile("griddepcontrol.launch_dependents;");
    const uint4* src = reinterpret_cast<const uint4*>(x + (size_t)row * DM);
    float v[16];
#pragma unroll
    for (int i = 0; i < 2; i++) {
        uint4 u = src[lane + i * 32];
        const __nv_bfloat162* h = reinterpret_cast<const __nv_bfloat162*>(&u);
#pragma unroll
        for (int j = 0; j < 4; j++) {
            float2 f = __bfloat1622float2(h[j]);
            v[i * 8 + j * 2] = f.x; v[i * 8 + j * 2 + 1] = f.y;
        }
    }
#pragma unroll
    for (int pass = 0; pass < 2; pass++) {
        float s = 0.f;
#pragma unroll
        for (int i = 0; i < 16; i++) s += v[i];
#pragma unroll
        for (int o = 16; o > 0; o >>= 1) s += __shfl_xor_sync(0xffffffffu, s, o);
        float mean = s * (1.f / DM);
        float q = 0.f;
#pragma unroll
        for (int i = 0; i < 16; i++) { float d = v[i] - mean; q += d * d; }
#pragma unroll
        for (int o = 16; o > 0; o >>= 1) q += __shfl_xor_sync(0xffffffffu, q, o);
        float rstd = 1.0f / sqrtf(q * (1.f / DM) + 1e-5f);
        bf16* dst = (pass == 0 ? g_xn : g_y) + (size_t)row * DM;
#pragma unroll
        for (int i = 0; i < 2; i++) {
            uint4 u;
            uint32_t* w = reinterpret_cast<uint32_t*>(&u);
#pragma unroll
            for (int j = 0; j < 4; j++) {
                __nv_bfloat162 h = __floats2bfloat162_rn((v[i * 8 + j * 2] - mean) * rstd, (v[i * 8 + j * 2 + 1] - mean) * rstd);
                w[j] = *reinterpret_cast<uint32_t*>(&h);
                float2 f = __bfloat1622float2(h);
                v[i * 8 + j * 2] = f.x; v[i * 8 + j * 2 + 1] = f.y;
            }
            reinterpret_cast<uint4*>(dst)[lane + i * 32] = u;
        }
    }
}

constexpr int G_STAGE_BYTES = 8192 + 16384;

__device__ __forceinline__ float gelu_tanh(float x) {
    float u = 0.7978845608028654f * (x + 0.044715f * x * x * x);
    float t = 1.f - __fdividef(2.f, 1.f + __expf(2.f * u));
    return 0.5f * x * (1.f + t);
}

constexpr int M1_STAGES = 4;
constexpr int M1_SMEM = M1_STAGES * G_STAGE_BYTES + 1024 + 256;
__global__ void __launch_bounds__(256, 2)
mlp1_kernel(const __grid_constant__ CUtensorMap mapA, const __grid_constant__ CUtensorMap mapB,
            bf16* __restrict__ C, const bf16* __restrict__ bias) {
    extern __shared__ uint8_t smem_raw[];
    uint32_t sbase = (smem_u32(smem_raw) + 1023) & ~1023u;
    uint32_t bar_full = sbase + M1_STAGES * G_STAGE_BYTES;
    uint32_t bar_empty = bar_full + 8 * M1_STAGES;
    int wg = threadIdx.x >> 7;
    int tid = threadIdx.x & 127;
    int m0 = blockIdx.y * 64, n0 = blockIdx.x * 128;
    constexpr int nk = DM / 64;

    if (threadIdx.x == 0) {
        for (int i = 0; i < M1_STAGES; i++) { mbar_init(bar_full + 8 * i, 1); mbar_init(bar_empty + 8 * i, 4); }
        fence_barrier_init();
    }
    __syncthreads();

    if (wg == 0) {
        if (tid == 0) {
            for (int it = 0; it < nk; it++) {
                int s = it % M1_STAGES;
                uint32_t ph = (it / M1_STAGES) & 1;
                mbar_wait(bar_empty + 8 * s, ph ^ 1);
                mbar_expect_tx(bar_full + 8 * s, G_STAGE_BYTES);
                uint32_t a = sbase + s * G_STAGE_BYTES;
                tma_load_2d(a, &mapA, bar_full + 8 * s, it * 64, m0);
                tma_load_2d(a + 8192, &mapB, bar_full + 8 * s, n0, it * 64);
                tma_load_2d(a + 8192 + 8192, &mapB, bar_full + 8 * s, n0 + 64, it * 64);
            }
        }
    } else {
        float acc[64];
        int warp = tid >> 5, lane = tid & 31;
        uint32_t bv[16];
#pragma unroll
        for (int j = 0; j < 16; j++) {
            int c = min(n0 + j * 8 + (lane & 3) * 2, FF - 2);
            bv[j] = *reinterpret_cast<const uint32_t*>(bias + c);
        }
        for (int it = 0; it < nk; it++) {
            int s = it % M1_STAGES;
            uint32_t ph = (it / M1_STAGES) & 1;
            mbar_wait(bar_full + 8 * s, ph);
            uint32_t a = sbase + s * G_STAGE_BYTES;
            uint32_t b = a + 8192;
            wgmma_fence();
#pragma unroll
            for (int kk = 0; kk < 4; kk++)
                wgmma_m64n128k16_ss<0, 1>(acc, make_desc(a + kk * 32, 16, 1024), make_desc(b + kk * 2048, 8192, 1024), (it | kk) != 0);
            wgmma_commit();
            wgmma_wait<1>();
            if (it > 0 && lane == 0) mbar_arrive(bar_empty + 8 * ((it - 1) % M1_STAGES));
        }
        wgmma_wait<0>();
        int r = warp * 16 + (lane >> 2);
#pragma unroll
        for (int j = 0; j < 16; j++) {
            float2 bf = __bfloat1622float2(*reinterpret_cast<const __nv_bfloat162*>(&bv[j]));
            float b0 = bf.x, b1 = bf.y;
            uint32_t a = sbase + r * 256 + ((j ^ (r & 7)) << 4) + (lane & 3) * 4;
            st_shared_u32(a, pack_bf16(gelu_tanh(acc[j * 4 + 0] + b0), gelu_tanh(acc[j * 4 + 1] + b1)));
            st_shared_u32(a + 2048, pack_bf16(gelu_tanh(acc[j * 4 + 2] + b0), gelu_tanh(acc[j * 4 + 3] + b1)));
        }
        named_sync(1, 128);
#pragma unroll
        for (int i = 0; i < 8; i++) {
            int idx = i * 128 + tid;
            int rr = idx >> 4, ch = idx & 15;
            uint4 v = ld_shared_v4(sbase + rr * 256 + ((ch ^ (rr & 7)) << 4));
            if (n0 + ch * 8 < FF)
                *reinterpret_cast<uint4*>(C + (size_t)(m0 + rr) * FF + n0 + ch * 8) = v;
        }
    }
}

constexpr int A_KV_STAGES = 2;
constexpr int A_TILE_BYTES = 128 * 128 * 2;
constexpr int A_SMEM = A_TILE_BYTES * (1 + 2 * A_KV_STAGES) + 1024 + 256;

__global__ void __launch_bounds__(384, 1)
attn_kernel(const __grid_constant__ CUtensorMap mapXn, const __grid_constant__ CUtensorMap mapWq,
            const __grid_constant__ CUtensorMap mapK, const __grid_constant__ CUtensorMap mapV) {
    extern __shared__ uint8_t smem_raw[];
    uint32_t sbase = (smem_u32(smem_raw) + 1023) & ~1023u;
    uint32_t sQ = sbase;
    uint32_t sK = sQ + A_TILE_BYTES;
    uint32_t sV = sK + A_KV_STAGES * A_TILE_BYTES;
    uint32_t bars = sV + A_KV_STAGES * A_TILE_BYTES;
    uint32_t bar_pf = bars, bar_pe = bars + 32;
    uint32_t bar_kf = bars + 64, bar_ke = bar_kf + 8 * A_KV_STAGES;
    uint32_t bar_vf = bar_ke + 8 * A_KV_STAGES, bar_ve = bar_vf + 8 * A_KV_STAGES;
    int wg = threadIdx.x >> 7;
    int tid = threadIdx.x & 127;
    int qt = blockIdx.x, head = blockIdx.y;
    constexpr int NT = SEQ / 128;

    if (threadIdx.x == 0) {
        for (int i = 0; i < 4; i++) { mbar_init(bar_pf + 8 * i, 1); mbar_init(bar_pe + 8 * i, 8); }
        for (int i = 0; i < A_KV_STAGES; i++) {
            mbar_init(bar_kf + 8 * i, 1); mbar_init(bar_ke + 8 * i, 8);
            mbar_init(bar_vf + 8 * i, 1); mbar_init(bar_ve + 8 * i, 8);
        }
        fence_barrier_init();
    }
    __syncthreads();
    asm volatile("griddepcontrol.wait;" ::: "memory");

    if (wg == 0) {
        reg_dealloc<40>();
        if (tid == 0) {
            for (int i = 0; i < 8; i++) {
                int b = i & 3;
                uint32_t buf = sK + b * A_TILE_BYTES;
                mbar_wait(bar_pe + 8 * b, ((i >> 2) & 1) ^ 1);
                mbar_expect_tx(bar_pf + 8 * b, A_TILE_BYTES);
                tma_load_2d(buf, &mapXn, bar_pf + 8 * b, i * 64, qt * 128);
                tma_load_2d(buf + 16384, &mapWq, bar_pf + 8 * b, head * DH, i * 64);
                tma_load_2d(buf + 16384 + 8192, &mapWq, bar_pf + 8 * b, head * DH + 64, i * 64);
            }
            for (int it = 0; it < NT; it++) {
                int s = it % A_KV_STAGES;
                uint32_t ph = (it / A_KV_STAGES) & 1;
                int row = head * SEQ + it * 128;
                if (it < A_KV_STAGES) mbar_wait(bar_pe + 8 * s, 1);
                else mbar_wait(bar_ke + 8 * s, ph ^ 1);
                mbar_expect_tx(bar_kf + 8 * s, A_TILE_BYTES);
                tma_load_2d(sK + s * A_TILE_BYTES, &mapK, bar_kf + 8 * s, 0, row);
                tma_load_2d(sK + s * A_TILE_BYTES + 16384, &mapK, bar_kf + 8 * s, 64, row);
                if (it < A_KV_STAGES) mbar_wait(bar_pe + 8 * (A_KV_STAGES + s), 1);
                else mbar_wait(bar_ve + 8 * s, ph ^ 1);
                mbar_expect_tx(bar_vf + 8 * s, A_TILE_BYTES);
                tma_load_2d(sV + s * A_TILE_BYTES, &mapV, bar_vf + 8 * s, 0, row);
                tma_load_2d(sV + s * A_TILE_BYTES + 16384, &mapV, bar_vf + 8 * s, 64, row);
            }
        }
    } else {
        reg_alloc<232>();
        int cw = wg - 1;
        int warp = tid >> 5, lane = tid & 31;
        float o[64];
        for (int i = 0; i < 8; i++) {
            int b = i & 3;
            uint32_t buf = sK + b * A_TILE_BYTES;
            mbar_wait(bar_pf + 8 * b, (i >> 2) & 1);
            wgmma_fence();
#pragma unroll
            for (int kk = 0; kk < 4; kk++)
                wgmma_m64n128k16_ss<0, 1>(o, make_desc(buf + cw * 8192 + kk * 32, 16, 1024),
                                          make_desc(buf + 16384 + kk * 2048, 8192, 1024), (i | kk) != 0);
            wgmma_commit();
            wgmma_wait<0>();
            if (lane == 0) mbar_arrive(bar_pe + 8 * b);
        }
        {
            int r = cw * 64 + warp * 16 + (lane >> 2);
#pragma unroll
            for (int j = 0; j < 16; j++) {
                uint32_t a = sQ + (j >> 3) * 16384 + r * 128 + (((j & 7) ^ (r & 7)) << 4) + (lane & 3) * 4;
                st_shared_u32(a, pack_bf16(o[j * 4 + 0], o[j * 4 + 1]));
                st_shared_u32(a + 1024, pack_bf16(o[j * 4 + 2], o[j * 4 + 3]));
            }
            fence_proxy_async();
            named_sync(3 + cw, 128);
        }
#pragma unroll
        for (int i = 0; i < 64; i++) o[i] = 0.f;
        float m0 = -INFINITY, m1 = -INFINITY, l0 = 0.f, l1 = 0.f;
        const float sc = 0.08838834764831845f * 1.4426950408889634f;
        if (cw == 1) named_arrive(1, 256);
        uint32_t qa = sQ + cw * 8192;
        float sacc[64];
        uint32_t p[32];
        mbar_wait(bar_kf, 0);
        named_sync(1 + cw, 256);
        wgmma_fence();
#pragma unroll
        for (int kk = 0; kk < 8; kk++) {
            uint32_t off = (kk >> 2) * 16384 + (kk & 3) * 32;
            wgmma_m64n128k16_ss<0, 0>(sacc, make_desc(qa + off, 16, 1024), make_desc(sK + off, 16, 1024), kk != 0);
        }
        wgmma_commit();
        named_arrive(1 + (cw ^ 1), 256);
        wgmma_wait<0>();
        if (lane == 0) mbar_arrive(bar_ke);
        {
            float mx0 = -INFINITY, mx1 = -INFINITY;
#pragma unroll
            for (int j = 0; j < 16; j++) {
                mx0 = fmaxf(mx0, fmaxf(sacc[j * 4 + 0], sacc[j * 4 + 1]));
                mx1 = fmaxf(mx1, fmaxf(sacc[j * 4 + 2], sacc[j * 4 + 3]));
            }
            mx0 = fmaxf(mx0, __shfl_xor_sync(0xffffffffu, mx0, 1));
            mx0 = fmaxf(mx0, __shfl_xor_sync(0xffffffffu, mx0, 2));
            mx1 = fmaxf(mx1, __shfl_xor_sync(0xffffffffu, mx1, 1));
            mx1 = fmaxf(mx1, __shfl_xor_sync(0xffffffffu, mx1, 2));
            m0 = mx0; m1 = mx1;
            float ms0 = mx0 * sc, ms1 = mx1 * sc;
#pragma unroll
            for (int j = 0; j < 16; j++) {
                float p0 = fast_exp2(sacc[j * 4 + 0] * sc - ms0);
                float p1 = fast_exp2(sacc[j * 4 + 1] * sc - ms0);
                float p2 = fast_exp2(sacc[j * 4 + 2] * sc - ms1);
                float p3 = fast_exp2(sacc[j * 4 + 3] * sc - ms1);
                l0 += p0 + p1; l1 += p2 + p3;
                p[j * 2 + 0] = pack_bf16(p0, p1);
                p[j * 2 + 1] = pack_bf16(p2, p3);
            }
        }
        for (int it = 1; it < NT; it++) {
            int s = it % A_KV_STAGES;
            uint32_t ph = (it / A_KV_STAGES) & 1;
            int sp = (it - 1) % A_KV_STAGES;
            uint32_t php = ((it - 1) / A_KV_STAGES) & 1;
            mbar_wait(bar_kf + 8 * s, ph);
            named_sync(1 + cw, 256);
            uint32_t kb = sK + s * A_TILE_BYTES;
            wgmma_fence();
#pragma unroll
            for (int kk = 0; kk < 8; kk++) {
                uint32_t off = (kk >> 2) * 16384 + (kk & 3) * 32;
                wgmma_m64n128k16_ss<0, 0>(sacc, make_desc(qa + off, 16, 1024), make_desc(kb + off, 16, 1024), kk != 0);
            }
            wgmma_commit();
            mbar_wait(bar_vf + 8 * sp, php);
            uint32_t vb = sV + sp * A_TILE_BYTES;
#pragma unroll
            for (int kk = 0; kk < 8; kk++) {
                wgmma_m64n128k16_rs<1>(o, p[kk * 4 + 0], p[kk * 4 + 1], p[kk * 4 + 2], p[kk * 4 + 3],
                                       make_desc(vb + kk * 2048, 16384, 1024), 1);
            }
            wgmma_commit();
            named_arrive(1 + (cw ^ 1), 256);
            wgmma_wait<1>();
            if (lane == 0) mbar_arrive(bar_ke + 8 * s);
            float mx0 = m0, mx1 = m1;
#pragma unroll
            for (int j = 0; j < 16; j++) {
                mx0 = fmaxf(mx0, fmaxf(sacc[j * 4 + 0], sacc[j * 4 + 1]));
                mx1 = fmaxf(mx1, fmaxf(sacc[j * 4 + 2], sacc[j * 4 + 3]));
            }
            mx0 = fmaxf(mx0, __shfl_xor_sync(0xffffffffu, mx0, 1));
            mx0 = fmaxf(mx0, __shfl_xor_sync(0xffffffffu, mx0, 2));
            mx1 = fmaxf(mx1, __shfl_xor_sync(0xffffffffu, mx1, 1));
            mx1 = fmaxf(mx1, __shfl_xor_sync(0xffffffffu, mx1, 2));
            float c0 = fast_exp2((m0 - mx0) * sc), c1 = fast_exp2((m1 - mx1) * sc);
            m0 = mx0; m1 = mx1;
            float ms0 = mx0 * sc, ms1 = mx1 * sc;
            float rs0 = 0.f, rs1 = 0.f;
#pragma unroll
            for (int j = 0; j < 16; j++) {
                sacc[j * 4 + 0] = fast_exp2(sacc[j * 4 + 0] * sc - ms0);
                sacc[j * 4 + 1] = fast_exp2(sacc[j * 4 + 1] * sc - ms0);
                sacc[j * 4 + 2] = fast_exp2(sacc[j * 4 + 2] * sc - ms1);
                sacc[j * 4 + 3] = fast_exp2(sacc[j * 4 + 3] * sc - ms1);
                rs0 += sacc[j * 4 + 0] + sacc[j * 4 + 1]; rs1 += sacc[j * 4 + 2] + sacc[j * 4 + 3];
            }
            l0 = l0 * c0 + rs0; l1 = l1 * c1 + rs1;
            wgmma_wait<0>();
            if (lane == 0) mbar_arrive(bar_ve + 8 * sp);
#pragma unroll
            for (int j = 0; j < 16; j++) {
                o[j * 4 + 0] *= c0; o[j * 4 + 1] *= c0; o[j * 4 + 2] *= c1; o[j * 4 + 3] *= c1;
                p[j * 2 + 0] = pack_bf16(sacc[j * 4 + 0], sacc[j * 4 + 1]);
                p[j * 2 + 1] = pack_bf16(sacc[j * 4 + 2], sacc[j * 4 + 3]);
            }
        }
        {
            int sp = (NT - 1) % A_KV_STAGES;
            uint32_t php = ((NT - 1) / A_KV_STAGES) & 1;
            mbar_wait(bar_vf + 8 * sp, php);
            uint32_t vb = sV + sp * A_TILE_BYTES;
            wgmma_fence();
#pragma unroll
            for (int kk = 0; kk < 8; kk++) {
                wgmma_m64n128k16_rs<1>(o, p[kk * 4 + 0], p[kk * 4 + 1], p[kk * 4 + 2], p[kk * 4 + 3],
                                       make_desc(vb + kk * 2048, 16384, 1024), 1);
            }
            wgmma_commit();
            wgmma_wait<0>();
        }
        l0 += __shfl_xor_sync(0xffffffffu, l0, 1);
        l0 += __shfl_xor_sync(0xffffffffu, l0, 2);
        l1 += __shfl_xor_sync(0xffffffffu, l1, 1);
        l1 += __shfl_xor_sync(0xffffffffu, l1, 2);
        float i0 = 1.f / l0, i1 = 1.f / l1;
        {
            int r = cw * 64 + warp * 16 + (lane >> 2);
#pragma unroll
            for (int j = 0; j < 16; j++) {
                uint32_t a = sQ + (j >> 3) * 16384 + r * 128 + (((j & 7) ^ (r & 7)) << 4) + (lane & 3) * 4;
                st_shared_u32(a, pack_bf16(o[j * 4 + 0] * i0, o[j * 4 + 1] * i0));
                st_shared_u32(a + 1024, pack_bf16(o[j * 4 + 2] * i1, o[j * 4 + 3] * i1));
            }
            named_sync(3 + cw, 128);
#pragma unroll
            for (int i = 0; i < 8; i++) {
                int idx = i * 128 + tid;
                int rr = cw * 64 + (idx >> 4), ch = idx & 15;
                uint32_t a = sQ + (ch >> 3) * 16384 + rr * 128 + (((ch & 7) ^ (rr & 7)) << 4);
                uint4 v = ld_shared_v4(a);
                *reinterpret_cast<uint4*>(g_o + (size_t)(qt * 128 + rr) * HD + head * DH + ch * 8) = v;
            }
        }
    }
}

constexpr int F_STAGES = 8;
constexpr int F_SMEM = F_STAGES * G_STAGE_BYTES + 1024 + 256;
__global__ void __launch_bounds__(256, 1)
final_kernel(const __grid_constant__ CUtensorMap mapO, const __grid_constant__ CUtensorMap mapWo,
             const __grid_constant__ CUtensorMap mapH, const __grid_constant__ CUtensorMap mapW2,
             const bf16* __restrict__ x, const bf16* __restrict__ b2, bf16* __restrict__ out) {
    extern __shared__ uint8_t smem_raw[];
    uint32_t sbase = (smem_u32(smem_raw) + 1023) & ~1023u;
    uint32_t bar_full = sbase + F_STAGES * G_STAGE_BYTES;
    uint32_t bar_empty = bar_full + 8 * F_STAGES;
    int wg = threadIdx.x >> 7;
    int tid = threadIdx.x & 127;
    int m0 = blockIdx.y * 64, n0 = blockIdx.x * 128;
    constexpr int NK1 = HD / 64;
    constexpr int NK2 = (FF + 63) / 64;

    if (threadIdx.x == 0) {
        for (int i = 0; i < F_STAGES; i++) { mbar_init(bar_full + 8 * i, 1); mbar_init(bar_empty + 8 * i, 4); }
        fence_barrier_init();
    }
    __syncthreads();

    if (wg == 0) {
        if (tid == 0) {
            for (int it = 0; it < NK1 + NK2; it++) {
                int s = it % F_STAGES;
                uint32_t ph = (it / F_STAGES) & 1;
                mbar_wait(bar_empty + 8 * s, ph ^ 1);
                mbar_expect_tx(bar_full + 8 * s, G_STAGE_BYTES);
                uint32_t a = sbase + s * G_STAGE_BYTES;
                const CUtensorMap* pa = it < NK2 ? &mapH : &mapO;
                const CUtensorMap* pb = it < NK2 ? &mapW2 : &mapWo;
                int k = (it < NK2 ? it : it - NK2) * 64;
                tma_load_2d(a, pa, bar_full + 8 * s, k, m0);
                tma_load_2d(a + 8192, pb, bar_full + 8 * s, n0, k);
                tma_load_2d(a + 8192 + 8192, pb, bar_full + 8 * s, n0 + 64, k);
            }
        }
    } else {
        float acc[64], acc2[64];
        int warp = tid >> 5, lane = tid & 31;
        int r = warp * 16 + (lane >> 2);
        uint32_t xv[32], bv[16];
#pragma unroll
        for (int j = 0; j < 16; j++) {
            int c = n0 + j * 8 + (lane & 3) * 2;
            bv[j] = *reinterpret_cast<const uint32_t*>(b2 + c);
            xv[j * 2] = *reinterpret_cast<const uint32_t*>(x + (size_t)(m0 + r) * DM + c);
            xv[j * 2 + 1] = *reinterpret_cast<const uint32_t*>(x + (size_t)(m0 + r + 8) * DM + c);
        }
        for (int it = 0; it < NK2; it++) {
            int s = it % F_STAGES;
            uint32_t ph = (it / F_STAGES) & 1;
            mbar_wait(bar_full + 8 * s, ph);
            uint32_t a = sbase + s * G_STAGE_BYTES;
            uint32_t b = a + 8192;
            wgmma_fence();
#pragma unroll
            for (int kk = 0; kk < 4; kk++)
                wgmma_m64n128k16_ss<0, 1>(acc2, make_desc(a + kk * 32, 16, 1024), make_desc(b + kk * 2048, 8192, 1024), (it | kk) != 0);
            wgmma_commit();
            wgmma_wait<1>();
            if (it > 0 && lane == 0) mbar_arrive(bar_empty + 8 * ((it - 1) % F_STAGES));
        }
        for (int it = NK2; it < NK1 + NK2; it++) {
            int s = it % F_STAGES;
            uint32_t ph = (it / F_STAGES) & 1;
            mbar_wait(bar_full + 8 * s, ph);
            uint32_t a = sbase + s * G_STAGE_BYTES;
            uint32_t b = a + 8192;
            wgmma_fence();
#pragma unroll
            for (int kk = 0; kk < 4; kk++)
                wgmma_m64n128k16_ss<0, 1>(acc, make_desc(a + kk * 32, 16, 1024), make_desc(b + kk * 2048, 8192, 1024), ((it - NK2) | kk) != 0);
            wgmma_commit();
            wgmma_wait<1>();
            if (lane == 0) mbar_arrive(bar_empty + 8 * ((it - 1) % F_STAGES));
        }
        wgmma_wait<0>();
#pragma unroll
        for (int j = 0; j < 16; j++) {
            float2 bf = __bfloat1622float2(*reinterpret_cast<const __nv_bfloat162*>(&bv[j]));
            uint32_t a = sbase + r * 256 + ((j ^ (r & 7)) << 4) + (lane & 3) * 4;
#pragma unroll
            for (int h = 0; h < 2; h++) {
                float2 xf = __bfloat1622float2(*reinterpret_cast<const __nv_bfloat162*>(&xv[j * 2 + h]));
                float g0 = acc2[j * 4 + h * 2 + 0] + bf.x, g1 = acc2[j * 4 + h * 2 + 1] + bf.y;
                g0 = __fdividef(g0, 1.f + __expf(-g0)); g1 = __fdividef(g1, 1.f + __expf(-g1));
                st_shared_u32(a + h * 2048, pack_bf16(xf.x + acc[j * 4 + h * 2 + 0] * g0, xf.y + acc[j * 4 + h * 2 + 1] * g1));
            }
        }
        named_sync(1, 128);
#pragma unroll
        for (int i = 0; i < 8; i++) {
            int idx = i * 128 + tid;
            int rr = idx >> 4, ch = idx & 15;
            uint4 v = ld_shared_v4(sbase + rr * 256 + ((ch ^ (rr & 7)) << 4));
            *reinterpret_cast<uint4*>(out + (size_t)(m0 + rr) * DM + n0 + ch * 8) = v;
        }
    }
}

typedef CUresult (*EncodeFn)(CUtensorMap*, CUtensorMapDataType, cuuint32_t, void*, const cuuint64_t*, const cuuint64_t*,
                             const cuuint32_t*, const cuuint32_t*, CUtensorMapInterleave, CUtensorMapSwizzle,
                             CUtensorMapL2promotion, CUtensorMapFloatOOBfill);

static void make_map(EncodeFn fn, CUtensorMap* m, const void* ptr, uint64_t inner, uint64_t outer,
                     uint32_t box_inner, uint32_t box_outer) {
    cuuint64_t dims[2] = {inner, outer};
    cuuint64_t strides[1] = {inner * 2};
    cuuint32_t box[2] = {box_inner, box_outer};
    cuuint32_t es[2] = {1, 1};
    fn(m, CU_TENSOR_MAP_DATA_TYPE_BFLOAT16, 2, const_cast<void*>(ptr), dims, strides, box, es,
       CU_TENSOR_MAP_INTERLEAVE_NONE, CU_TENSOR_MAP_SWIZZLE_128B, CU_TENSOR_MAP_L2_PROMOTION_L2_256B,
       CU_TENSOR_MAP_FLOAT_OOB_FILL_NONE);
}

extern "C" void kernel_launch(void* const* d_in, const int* in_sizes, int n_in, void* d_out, int out_size) {
    const bf16* x  = (const bf16*)d_in[0];
    const bf16* kc = (const bf16*)d_in[1];
    const bf16* vc = (const bf16*)d_in[2];
    const bf16* wq = (const bf16*)d_in[3];
    const bf16* wo = (const bf16*)d_in[4];
    const bf16* w1 = (const bf16*)d_in[6];
    const bf16* b1 = (const bf16*)d_in[7];
    const bf16* w2 = (const bf16*)d_in[8];
    const bf16* b2 = (const bf16*)d_in[9];
    bf16* out = (bf16*)d_out;

    static bool inited = false;
    static CUtensorMap mXn, mY, mWq, mW1, mQ, mK, mV, mO, mWo, mH, mW2;
    static void *pq, *ph;
    static cudaStream_t s2;
    static cudaEvent_t evFork, evJoin;
    if (!inited) {
        EncodeFn fn = nullptr;
        cudaDriverEntryPointQueryResult qres;
        cudaGetDriverEntryPoint("cuTensorMapEncodeTiled", (void**)&fn, cudaEnableDefault, &qres);
        void *pxn, *py, *po;
        cudaGetSymbolAddress(&pxn, g_xn); cudaGetSymbolAddress(&py, g_y); cudaGetSymbolAddress(&pq, g_q);
        cudaGetSymbolAddress(&ph, g_h); cudaGetSymbolAddress(&po, g_o);
        make_map(fn, &mXn, pxn, DM, SEQ, 64, 128);
        make_map(fn, &mY, py, DM, SEQ, 64, 64);
        make_map(fn, &mWq, wq, HD, DM, 64, 64);
        make_map(fn, &mW1, w1, FF, DM, 64, 64);
        make_map(fn, &mK, kc, DH, NH * SEQ, 64, 128);
        make_map(fn, &mV, vc, DH, NH * SEQ, 64, 128);
        make_map(fn, &mO, po, HD, SEQ, 64, 64);
        make_map(fn, &mWo, wo, DM, HD, 64, 64);
        make_map(fn, &mH, ph, FF, SEQ, 64, 64);
        make_map(fn, &mW2, w2, DM, FF, 64, 64);
        cudaFuncSetAttribute(mlp1_kernel, cudaFuncAttributeMaxDynamicSharedMemorySize, M1_SMEM);
        cudaFuncSetAttribute(final_kernel, cudaFuncAttributeMaxDynamicSharedMemorySize, F_SMEM);
        cudaFuncSetAttribute(attn_kernel, cudaFuncAttributeMaxDynamicSharedMemorySize, A_SMEM);
        cudaStreamCreateWithFlags(&s2, cudaStreamNonBlocking);
        cudaEventCreateWithFlags(&evFork, cudaEventDisableTiming);
        cudaEventCreateWithFlags(&evJoin, cudaEventDisableTiming);
        inited = true;
    }

    ln_kernel<<<SEQ / 8, 256>>>(x);
    cudaEventRecord(evFork, cudaStreamPerThread);
    {
        cudaLaunchConfig_t cfg = {};
        cfg.gridDim = dim3(SEQ / 128, NH); cfg.blockDim = dim3(384); cfg.dynamicSmemBytes = A_SMEM;
        cfg.stream = cudaStreamPerThread;
        cudaLaunchAttribute at[1];
        at[0].id = cudaLaunchAttributeProgrammaticStreamSerialization;
        at[0].val.programmaticStreamSerializationAllowed = 1;
        cfg.attrs = at; cfg.numAttrs = 1;
        cudaLaunchKernelEx(&cfg, attn_kernel, mXn, mWq, mK, mV);
    }
    cudaStreamWaitEvent(s2, evFork, 0);
    mlp1_kernel<<<dim3((FF + 127) / 128, SEQ / 64), 256, M1_SMEM, s2>>>(mY, mW1, (bf16*)ph, b1);
    cudaEventRecord(evJoin, s2);
    cudaStreamWaitEvent(cudaStreamPerThread, evJoin, 0);
    final_kernel<<<dim3(DM / 128, SEQ / 64), 256, F_SMEM>>>(mO, mWo, mH, mW2, x, b2, out);
}
```
